```python
import torch

def _softmax(x, axis=-1):
    return torch.softmax(x, dim=axis)
def _gelu(x):
    return torch.nn.functional.gelu(x, approximate="tanh")
def _silu(x):
    return torch.nn.functional.silu(x)
def _sigmoid(x):
    return torch.sigmoid(x)
def _layernorm(x, axis=-1, eps=1e-5):
    m = x.mean(dim=axis, keepdim=True)
    v = x.var(dim=axis, keepdim=True, unbiased=False)
    return (x - m) / torch.sqrt(v + eps)
def _scatter_add(tgt, idx, src, axis=0):
    return tgt.clone().index_add_(axis, idx, src)
def _segment_sum(src, seg, n):
    out = torch.zeros((n,) + src.shape[1:], dtype=src.dtype)
    return out.index_add_(0, seg, src)
def _pad(x, pw):
    flat = tuple(v for pair in reversed(pw) for v in pair)
    return torch.nn.functional.pad(x, flat)

kernel_name = 'recurrent_scan__ssm_conv_s4d__mixer_channel_mlp__prompt'

def setup_inputs():

    _w = (lambda a: (lambda t: t.to(torch.bfloat16) if t.is_floating_point() else t)(torch.as_tensor(a)))
    def _A_setup():
        Bsz, L, D, N = 1, 2048, 640, 128
        return {
            "u": _w((lambda *s: torch.randn(*s, dtype=torch.bfloat16) * 0.05)(Bsz, L, D)),
            "log_A_real": _w((lambda *s: torch.randn(*s, dtype=torch.bfloat16) * 3.2)(D, N) * 0.5),
            "A_imag": _w((lambda *s: torch.randn(*s, dtype=torch.bfloat16) * 0.2)(D, N) * 3.14),
            "C_real": _w((lambda *s: torch.randn(*s, dtype=torch.bfloat16) * 0.8)(D, N) / N ** 0.5),
            "C_imag": _w((lambda *s: torch.randn(*s, dtype=torch.bfloat16) * 0.8)(D, N) / N ** 0.5),
            "log_dt": _w((lambda *s: torch.randn(*s, dtype=torch.bfloat16) * 0.2)(D) * 0.5 - 4.0),
            "D_skip": _w((lambda *s: torch.randn(*s, dtype=torch.bfloat16) * 0.2)(D)),
        }
    _A_in = _A_setup()

    def _B_setup():
        B, S, D, F = 1, 2048, 640, 1728
        return {
            "x": _w((lambda *s: torch.randn(*s, dtype=torch.bfloat16) * 0.05)(B, S, D)),
            "w1": _w((lambda *s: torch.randn(*s, dtype=torch.bfloat16) * 1.6)(D, F) * (D ** -0.5)),
            "b1": _w((lambda *s: torch.randn(*s, dtype=torch.bfloat16) * 0.8)(F)),
            "w2": _w((lambda *s: torch.randn(*s, dtype=torch.bfloat16) * 0.1)(F, D) * (F ** -0.5)),
            "b2": _w((lambda *s: torch.randn(*s, dtype=torch.bfloat16) * 0.1)(D)),
        }
    _B_in = _B_setup()

    return {
        "A_u": _A_in["u"],
        "A_log_A_real": _A_in["log_A_real"],
        "A_A_imag": _A_in["A_imag"],
        "A_C_real": _A_in["C_real"],
        "A_C_imag": _A_in["C_imag"],
        "A_log_dt": _A_in["log_dt"],
        "A_D_skip": _A_in["D_skip"],
        "B_x": _B_in["x"],
        "B_w1": _B_in["w1"],
        "B_b1": _B_in["b1"],
        "B_w2": _B_in["w2"],
        "B_b2": _B_in["b2"],
    }

def reference(A_u, A_log_A_real, A_A_imag, A_C_real, A_C_imag, A_log_dt, A_D_skip, B_x, B_w1, B_b1, B_w2, B_b2):
    def _A_ref(u, log_A_real, A_imag, C_real, C_imag, log_dt, D_skip):
        L = u.shape[1]
        dt = torch.exp(log_dt)
        A = -torch.exp(log_A_real) + 1j * A_imag
        C = (C_real + 1j * C_imag) * dt[:, None]
        pos = (lambda x, dt: x.to(dt))(torch.arange(L), log_dt.dtype)
        P = torch.exp((A * dt[:, None])[:, :, None] * pos[None, None, :])
        K = 2.0 * torch.einsum("dn,dnl->dl", C, P).real
        L2 = 2 * L
        u_t = (lambda x, *d: x.permute(*d))(u, 0, 2, 1)
        Kf = (lambda x, *a, **k: torch.fft.rfft(x.float(), *a, **k))(K, L2)
        Uf = (lambda x, *a, **k: torch.fft.rfft(x.float(), *a, **k))(u_t, L2)
        y = (lambda x, *a, **k: torch.fft.irfft(x, *a, **k).to(torch.bfloat16))(Uf * Kf[None, :, :], L2)[:, :, :L]
        y = (lambda x, *d: x.permute(*d))(y, 0, 2, 1)
        return y + u * D_skip[None, None, :]

    def _B_ref(x, w1, b1, w2, b2):
        y = _layernorm(x, axis=-1)
        h = _gelu(torch.einsum("bsd,df->bsf", y, w1) + b1)
        return torch.einsum("bsf,fd->bsd", h, w2) + b2

    x = A_u
    xn = _layernorm(x, axis=-1)
    s = _A_ref(xn, A_log_A_real, A_A_imag, A_C_real, A_C_imag, A_log_dt, A_D_skip)
    g = _silu(_B_ref(xn, B_w1, B_b1, B_w2, B_b2))
    return x + s * g
```

```cpp
#include <cuda_runtime.h>
#include <cuda_bf16.h>
#include <cuda.h>
#include <stdint.h>

__device__ __forceinline__ void wg_ss_80(float* d, uint64_t da, uint64_t db){
  asm volatile("wgmma.mma_async.sync.aligned.m64n80k16.f32.bf16.bf16 {%0,%1,%2,%3,%4,%5,%6,%7,%8,%9,%10,%11,%12,%13,%14,%15,%16,%17,%18,%19,%20,%21,%22,%23,%24,%25,%26,%27,%28,%29,%30,%31,%32,%33,%34,%35,%36,%37,%38,%39},%40,%41,1,1,1,0,1;"
    :"+f"(d[0]),"+f"(d[1]),"+f"(d[2]),"+f"(d[3]),"+f"(d[4]),"+f"(d[5]),"+f"(d[6]),"+f"(d[7]),"+f"(d[8]),"+f"(d[9]),"+f"(d[10]),"+f"(d[11]),"+f"(d[12]),"+f"(d[13]),"+f"(d[14]),"+f"(d[15]),"+f"(d[16]),"+f"(d[17]),"+f"(d[18]),"+f"(d[19]),"+f"(d[20]),"+f"(d[21]),"+f"(d[22]),"+f"(d[23]),"+f"(d[24]),"+f"(d[25]),"+f"(d[26]),"+f"(d[27]),"+f"(d[28]),"+f"(d[29]),"+f"(d[30]),"+f"(d[31]),"+f"(d[32]),"+f"(d[33]),"+f"(d[34]),"+f"(d[35]),"+f"(d[36]),"+f"(d[37]),"+f"(d[38]),"+f"(d[39])
    :"l"(da),"l"(db));
}
__device__ __forceinline__ void wg_ss_96(float* d, uint64_t da, uint64_t db){
  asm volatile("wgmma.mma_async.sync.aligned.m64n96k16.f32.bf16.bf16 {%0,%1,%2,%3,%4,%5,%6,%7,%8,%9,%10,%11,%12,%13,%14,%15,%16,%17,%18,%19,%20,%21,%22,%23,%24,%25,%26,%27,%28,%29,%30,%31,%32,%33,%34,%35,%36,%37,%38,%39,%40,%41,%42,%43,%44,%45,%46,%47},%48,%49,1,1,1,0,1;"
    :"+f"(d[0]),"+f"(d[1]),"+f"(d[2]),"+f"(d[3]),"+f"(d[4]),"+f"(d[5]),"+f"(d[6]),"+f"(d[7]),"+f"(d[8]),"+f"(d[9]),"+f"(d[10]),"+f"(d[11]),"+f"(d[12]),"+f"(d[13]),"+f"(d[14]),"+f"(d[15]),"+f"(d[16]),"+f"(d[17]),"+f"(d[18]),"+f"(d[19]),"+f"(d[20]),"+f"(d[21]),"+f"(d[22]),"+f"(d[23]),"+f"(d[24]),"+f"(d[25]),"+f"(d[26]),"+f"(d[27]),"+f"(d[28]),"+f"(d[29]),"+f"(d[30]),"+f"(d[31]),"+f"(d[32]),"+f"(d[33]),"+f"(d[34]),"+f"(d[35]),"+f"(d[36]),"+f"(d[37]),"+f"(d[38]),"+f"(d[39]),"+f"(d[40]),"+f"(d[41]),"+f"(d[42]),"+f"(d[43]),"+f"(d[44]),"+f"(d[45]),"+f"(d[46]),"+f"(d[47])
    :"l"(da),"l"(db));
}
__device__ __forceinline__ void wg_ss_128(float* d, uint64_t da, uint64_t db){
  asm volatile("wgmma.mma_async.sync.aligned.m64n128k16.f32.bf16.bf16 {%0,%1,%2,%3,%4,%5,%6,%7,%8,%9,%10,%11,%12,%13,%14,%15,%16,%17,%18,%19,%20,%21,%22,%23,%24,%25,%26,%27,%28,%29,%30,%31,%32,%33,%34,%35,%36,%37,%38,%39,%40,%41,%42,%43,%44,%45,%46,%47,%48,%49,%50,%51,%52,%53,%54,%55,%56,%57,%58,%59,%60,%61,%62,%63},%64,%65,1,1,1,0,1;"
    :"+f"(d[0]),"+f"(d[1]),"+f"(d[2]),"+f"(d[3]),"+f"(d[4]),"+f"(d[5]),"+f"(d[6]),"+f"(d[7]),"+f"(d[8]),"+f"(d[9]),"+f"(d[10]),"+f"(d[11]),"+f"(d[12]),"+f"(d[13]),"+f"(d[14]),"+f"(d[15]),"+f"(d[16]),"+f"(d[17]),"+f"(d[18]),"+f"(d[19]),"+f"(d[20]),"+f"(d[21]),"+f"(d[22]),"+f"(d[23]),"+f"(d[24]),"+f"(d[25]),"+f"(d[26]),"+f"(d[27]),"+f"(d[28]),"+f"(d[29]),"+f"(d[30]),"+f"(d[31]),"+f"(d[32]),"+f"(d[33]),"+f"(d[34]),"+f"(d[35]),"+f"(d[36]),"+f"(d[37]),"+f"(d[38]),"+f"(d[39]),"+f"(d[40]),"+f"(d[41]),"+f"(d[42]),"+f"(d[43]),"+f"(d[44]),"+f"(d[45]),"+f"(d[46]),"+f"(d[47]),"+f"(d[48]),"+f"(d[49]),"+f"(d[50]),"+f"(d[51]),"+f"(d[52]),"+f"(d[53]),"+f"(d[54]),"+f"(d[55]),"+f"(d[56]),"+f"(d[57]),"+f"(d[58]),"+f"(d[59]),"+f"(d[60]),"+f"(d[61]),"+f"(d[62]),"+f"(d[63])
    :"l"(da),"l"(db));
}
__device__ __forceinline__ void wg_ss_160(float* d, uint64_t da, uint64_t db){
  asm volatile("wgmma.mma_async.sync.aligned.m64n160k16.f32.bf16.bf16 {%0,%1,%2,%3,%4,%5,%6,%7,%8,%9,%10,%11,%12,%13,%14,%15,%16,%17,%18,%19,%20,%21,%22,%23,%24,%25,%26,%27,%28,%29,%30,%31,%32,%33,%34,%35,%36,%37,%38,%39,%40,%41,%42,%43,%44,%45,%46,%47,%48,%49,%50,%51,%52,%53,%54,%55,%56,%57,%58,%59,%60,%61,%62,%63,%64,%65,%66,%67,%68,%69,%70,%71,%72,%73,%74,%75,%76,%77,%78,%79},%80,%81,1,1,1,0,1;"
    :"+f"(d[0]),"+f"(d[1]),"+f"(d[2]),"+f"(d[3]),"+f"(d[4]),"+f"(d[5]),"+f"(d[6]),"+f"(d[7]),"+f"(d[8]),"+f"(d[9]),"+f"(d[10]),"+f"(d[11]),"+f"(d[12]),"+f"(d[13]),"+f"(d[14]),"+f"(d[15]),"+f"(d[16]),"+f"(d[17]),"+f"(d[18]),"+f"(d[19]),"+f"(d[20]),"+f"(d[21]),"+f"(d[22]),"+f"(d[23]),"+f"(d[24]),"+f"(d[25]),"+f"(d[26]),"+f"(d[27]),"+f"(d[28]),"+f"(d[29]),"+f"(d[30]),"+f"(d[31]),"+f"(d[32]),"+f"(d[33]),"+f"(d[34]),"+f"(d[35]),"+f"(d[36]),"+f"(d[37]),"+f"(d[38]),"+f"(d[39]),"+f"(d[40]),"+f"(d[41]),"+f"(d[42]),"+f"(d[43]),"+f"(d[44]),"+f"(d[45]),"+f"(d[46]),"+f"(d[47]),"+f"(d[48]),"+f"(d[49]),"+f"(d[50]),"+f"(d[51]),"+f"(d[52]),"+f"(d[53]),"+f"(d[54]),"+f"(d[55]),"+f"(d[56]),"+f"(d[57]),"+f"(d[58]),"+f"(d[59]),"+f"(d[60]),"+f"(d[61]),"+f"(d[62]),"+f"(d[63]),"+f"(d[64]),"+f"(d[65]),"+f"(d[66]),"+f"(d[67]),"+f"(d[68]),"+f"(d[69]),"+f"(d[70]),"+f"(d[71]),"+f"(d[72]),"+f"(d[73]),"+f"(d[74]),"+f"(d[75]),"+f"(d[76]),"+f"(d[77]),"+f"(d[78]),"+f"(d[79])
    :"l"(da),"l"(db));
}
__device__ __forceinline__ void wg_rs_48(float* d, uint32_t a0, uint32_t a1, uint32_t a2, uint32_t a3, uint64_t db){
  asm volatile("wgmma.mma_async.sync.aligned.m64n48k16.f32.bf16.bf16 {%0,%1,%2,%3,%4,%5,%6,%7,%8,%9,%10,%11,%12,%13,%14,%15,%16,%17,%18,%19,%20,%21,%22,%23},{%24,%25,%26,%27},%28,1,1,1,0;"
    :"+f"(d[0]),"+f"(d[1]),"+f"(d[2]),"+f"(d[3]),"+f"(d[4]),"+f"(d[5]),"+f"(d[6]),"+f"(d[7]),"+f"(d[8]),"+f"(d[9]),"+f"(d[10]),"+f"(d[11]),"+f"(d[12]),"+f"(d[13]),"+f"(d[14]),"+f"(d[15]),"+f"(d[16]),"+f"(d[17]),"+f"(d[18]),"+f"(d[19]),"+f"(d[20]),"+f"(d[21]),"+f"(d[22]),"+f"(d[23])
    :"r"(a0),"r"(a1),"r"(a2),"r"(a3),"l"(db));
}
__device__ __forceinline__ void wg_rs_64(float* d, uint32_t a0, uint32_t a1, uint32_t a2, uint32_t a3, uint64_t db){
  asm volatile("wgmma.mma_async.sync.aligned.m64n64k16.f32.bf16.bf16 {%0,%1,%2,%3,%4,%5,%6,%7,%8,%9,%10,%11,%12,%13,%14,%15,%16,%17,%18,%19,%20,%21,%22,%23,%24,%25,%26,%27,%28,%29,%30,%31},{%32,%33,%34,%35},%36,1,1,1,0;"
    :"+f"(d[0]),"+f"(d[1]),"+f"(d[2]),"+f"(d[3]),"+f"(d[4]),"+f"(d[5]),"+f"(d[6]),"+f"(d[7]),"+f"(d[8]),"+f"(d[9]),"+f"(d[10]),"+f"(d[11]),"+f"(d[12]),"+f"(d[13]),"+f"(d[14]),"+f"(d[15]),"+f"(d[16]),"+f"(d[17]),"+f"(d[18]),"+f"(d[19]),"+f"(d[20]),"+f"(d[21]),"+f"(d[22]),"+f"(d[23]),"+f"(d[24]),"+f"(d[25]),"+f"(d[26]),"+f"(d[27]),"+f"(d[28]),"+f"(d[29]),"+f"(d[30]),"+f"(d[31])
    :"r"(a0),"r"(a1),"r"(a2),"r"(a3),"l"(db));
}

__device__ __align__(1024) uint4 g_xnT[128 * 640 * 2];
__device__ __align__(1024) uint4 g_H[16 * 216 * 128];
__device__ __align__(1024) uint4 g_sT[640 * 256];
__device__ __align__(128) float2 g_stats[2048];
__device__ __align__(128) float g_csp[16 * 1728];
__device__ __align__(128) unsigned g_ep[128];
__device__ __align__(128) unsigned g_cnt_ln[32];
__device__ __align__(128) unsigned g_cnt_s[8 * 32];
__device__ __align__(128) unsigned g_flagH[128 * 8];
#define STAMP(i) do { } while (0)

struct Params {
  CUtensorMap mx, mw1a, mw1b[8], mw2a, mw2b[4], ms;
  const __nv_bfloat16 *x, *logA, *Aim, *Cre, *Cim, *logdt, *Dsk, *w1, *b1, *w2, *b2;
  __nv_bfloat16* out;
};

constexpr uint32_t OFF_A = 0, OFF_B = 49152, OFF_HST = 0, OFF_W = 65536, OFF_SLOT4 = 114688, OFF_SLOT0 = 132096, SLOT_SZ = 17408;
constexpr uint32_t OFF_KT = 201728, OFF_CB = 222208, OFF_ST = 224000, OFF_BAR = 225024, SMEM_BYTES = 225536;
constexpr uint32_t OFF_S = 0, OFF_X = 20480;
constexpr uint32_t UPS = 1184, S_F3 = 4736, S_F5 = 7824, S_F7 = 10912, S_F9 = 12960, S_G = 15024, GPS = 544, S_RED = 4880;
constexpr uint32_t B_FA = 0, B_FB = 24, B_FW = 64, B_FH = 96, B_EH = 144, B_SF = 192, B_XF = 200, B_XR = 208, B_S0 = 216, B_OD = 224, B_C1 = 256, B_C2 = 352;

__device__ __forceinline__ void mbar_init(uint32_t b, uint32_t c) { asm volatile("mbarrier.init.shared::cta.b64 [%0], %1;" ::"r"(b), "r"(c) : "memory"); }
__device__ __forceinline__ void mbar_expect(uint32_t b, uint32_t bytes) { asm volatile("mbarrier.arrive.expect_tx.shared::cta.b64 _, [%0], %1;" ::"r"(b), "r"(bytes) : "memory"); }
__device__ __forceinline__ void mbar_arrive(uint32_t b) { asm volatile("mbarrier.arrive.shared::cta.b64 _, [%0];" ::"r"(b) : "memory"); }
__device__ __forceinline__ void mbar_arrive_cl(uint32_t rb) { asm volatile("mbarrier.arrive.release.cluster.shared::cluster.b64 _, [%0];" ::"r"(rb) : "memory"); }
__device__ __forceinline__ uint32_t mapa(uint32_t a, uint32_t cta) { uint32_t r; asm volatile("mapa.shared::cluster.u32 %0,%1,%2;" : "=r"(r) : "r"(a), "r"(cta)); return r; }
__device__ __forceinline__ void mbar_wait(uint32_t b, uint32_t ph) {
  asm volatile("{.reg .pred p; .reg .u32 c; mov.u32 c,0;\n"
               "LW%=: mbarrier.try_wait.parity.shared::cta.b64 p,[%0],%1; @p bra LD%=; add.u32 c,c,1; setp.lt.u32 p,c,4000000; @p bra LW%=; trap;\n LD%=: }" ::"r"(b), "r"(ph) : "memory");
}
__device__ __forceinline__ void mbar_wait_cl(uint32_t b, uint32_t ph) {
  asm volatile("{.reg .pred p; .reg .u32 c; mov.u32 c,0;\n"
               "LW%=: mbarrier.try_wait.parity.acquire.cluster.shared::cta.b64 p,[%0],%1; @p bra LD%=; add.u32 c,c,1; setp.lt.u32 p,c,4000000; @p bra LW%=; trap;\n LD%=: }" ::"r"(b), "r"(ph) : "memory");
}
__device__ __forceinline__ void poll_ge(const unsigned* p, unsigned target) {
  asm volatile("{.reg .pred p; .reg .u32 c,v; .reg .s32 df; mov.u32 c,0;\n"
               "LP%=: ld.acquire.gpu.global.u32 v,[%0]; sub.s32 df,v,%1; setp.ge.s32 p,df,0; @p bra LQ%=; add.u32 c,c,1; setp.lt.u32 p,c,4000000; @p bra LP%=; trap;\n LQ%=: }" ::"l"(p), "r"(target) : "memory");
}
__device__ __forceinline__ void tma2d(uint32_t dst, const CUtensorMap* tm, uint32_t bar, int c0, int c1) {
  asm volatile("cp.async.bulk.tensor.2d.shared::cluster.global.mbarrier::complete_tx::bytes [%0],[%1,{%3,%4}],[%2];" ::"r"(dst), "l"(tm), "r"(bar), "r"(c0), "r"(c1) : "memory");
}
__device__ __forceinline__ void tma3d(uint32_t dst, const CUtensorMap* tm, uint32_t bar, int c0, int c1, int c2) {
  asm volatile("cp.async.bulk.tensor.3d.shared::cluster.global.mbarrier::complete_tx::bytes [%0],[%1,{%3,%4,%5}],[%2];" ::"r"(dst), "l"(tm), "r"(bar), "r"(c0), "r"(c1), "r"(c2) : "memory");
}
__device__ __forceinline__ void bulk_ld(uint32_t dst, const void* src, uint32_t bytes, uint32_t bar) {
  asm volatile("cp.async.bulk.shared::cluster.global.mbarrier::complete_tx::bytes [%0],[%1],%2,[%3];" ::"r"(dst), "l"(src), "r"(bytes), "r"(bar) : "memory");
}
__device__ __forceinline__ void bulk_st(void* dst, uint32_t src, uint32_t bytes) {
  asm volatile("cp.async.bulk.global.shared::cta.bulk_group [%0],[%1],%2;\n cp.async.bulk.commit_group;" ::"l"(dst), "r"(src), "r"(bytes) : "memory");
}
__device__ __forceinline__ uint32_t elect() { uint32_t el; asm volatile("{.reg .pred p; elect.sync _|p,0xffffffff; selp.u32 %0,1,0,p;}" : "=r"(el)); return el; }
__device__ __forceinline__ uint32_t atom_inc(uint32_t a) { uint32_t o; asm volatile("atom.shared.add.u32 %0,[%1],1;" : "=r"(o) : "r"(a) : "memory"); return o; }
#define BAR_SYNC(id, n) asm volatile("bar.sync %0,%1;" ::"r"(id), "n"(n) : "memory")
#define BAR_ARRIVE(id, n) asm volatile("bar.arrive %0,%1;" ::"r"(id), "n"(n) : "memory")
#define FENCE_ASYNC() asm volatile("fence.proxy.async;" ::: "memory")
#define FENCE_ASYNC_SH() asm volatile("fence.proxy.async.shared::cta;" ::: "memory")
#define WG_FENCE() asm volatile("wgmma.fence.sync.aligned;" ::: "memory")
#define WG_COMMIT() asm volatile("wgmma.commit_group.sync.aligned;" ::: "memory")
#define WG_WAIT(n) asm volatile("wgmma.wait_group.sync.aligned %0;" ::"n"(n) : "memory")
__device__ __forceinline__ uint64_t mkdesc(uint32_t addr, uint32_t lbo, uint32_t sbo, uint32_t type) {
  return ((uint64_t)type << 62) | ((uint64_t)sbo << 32) | ((uint64_t)lbo << 16) | (uint64_t)((addr & 0x3FFFF) >> 4);
}
__device__ __forceinline__ uint32_t pack(float lo, float hi) { uint32_t r; asm("cvt.rn.bf16x2.f32 %0,%1,%2;" : "=r"(r) : "f"(hi), "f"(lo)); return r; }
__device__ __forceinline__ float blo(uint32_t v) { return __uint_as_float(v << 16); }
__device__ __forceinline__ float bhi(uint32_t v) { return __uint_as_float(v & 0xffff0000u); }
__device__ __forceinline__ float tanh_ap(float x) { float r; asm("tanh.approx.f32 %0,%1;" : "=f"(r) : "f"(x)); return r; }
__device__ __forceinline__ float ex2(float x) { float r; asm("ex2.approx.f32 %0,%1;" : "=f"(r) : "f"(x)); return r; }
__device__ __forceinline__ uint32_t lds32(uint32_t a) { uint32_t v; asm volatile("ld.shared.b32 %0,[%1];" : "=r"(v) : "r"(a) : "memory"); return v; }
__device__ __forceinline__ float ldsf(uint32_t a) { float v; asm volatile("ld.shared.f32 %0,[%1];" : "=f"(v) : "r"(a) : "memory"); return v; }
__device__ __forceinline__ float4 lds128f(uint32_t a) { float4 v; asm volatile("ld.shared.v4.f32 {%0,%1,%2,%3},[%4];" : "=f"(v.x), "=f"(v.y), "=f"(v.z), "=f"(v.w) : "r"(a) : "memory"); return v; }
__device__ __forceinline__ void sts32(uint32_t a, uint32_t v) { asm volatile("st.shared.b32 [%0],%1;" ::"r"(a), "r"(v) : "memory"); }
__device__ __forceinline__ void stsf(uint32_t a, float v) { asm volatile("st.shared.f32 [%0],%1;" ::"r"(a), "f"(v) : "memory"); }
__device__ __forceinline__ void sts16(uint32_t a, uint32_t v) { asm volatile("st.shared.b16 [%0],%1;" ::"r"(a), "h"((uint16_t)v) : "memory"); }
__device__ __forceinline__ void sts128(uint32_t a, uint32_t x, uint32_t y, uint32_t z, uint32_t w) { asm volatile("st.shared.v4.b32 [%0],{%1,%2,%3,%4};" ::"r"(a), "r"(x), "r"(y), "r"(z), "r"(w) : "memory"); }
__device__ __forceinline__ void sts128f(uint32_t a, float x, float y, float z, float w) { asm volatile("st.shared.v4.f32 [%0],{%1,%2,%3,%4};" ::"r"(a), "f"(x), "f"(y), "f"(z), "f"(w) : "memory"); }
__device__ __forceinline__ void ldsm4t(uint32_t* r, uint32_t a) { asm volatile("ldmatrix.sync.aligned.m8n8.x4.trans.shared.b16 {%0,%1,%2,%3},[%4];" : "=r"(r[0]), "=r"(r[1]), "=r"(r[2]), "=r"(r[3]) : "r"(a) : "memory"); }
__device__ __forceinline__ void stsm4(uint32_t a, uint32_t r0, uint32_t r1, uint32_t r2, uint32_t r3) { asm volatile("stmatrix.sync.aligned.m8n8.x4.shared.b16 [%0],{%1,%2,%3,%4};" ::"r"(a), "r"(r0), "r"(r1), "r"(r2), "r"(r3) : "memory"); }
__device__ __forceinline__ void stsm4t(uint32_t a, uint32_t r0, uint32_t r1, uint32_t r2, uint32_t r3) { asm volatile("stmatrix.sync.aligned.m8n8.x4.trans.shared.b16 [%0],{%1,%2,%3,%4};" ::"r"(a), "r"(r0), "r"(r1), "r"(r2), "r"(r3) : "memory"); }
__device__ __forceinline__ void mma16(float* c, const uint32_t* a, uint32_t b0, uint32_t b1) {
  asm volatile("mma.sync.aligned.m16n8k16.row.col.f32.bf16.bf16.f32 {%0,%1,%2,%3},{%4,%5,%6,%7},{%8,%9},{%0,%1,%2,%3};" : "+f"(c[0]), "+f"(c[1]), "+f"(c[2]), "+f"(c[3]) : "r"(a[0]), "r"(a[1]), "r"(a[2]), "r"(a[3]), "r"(b0), "r"(b1));
}
__device__ __forceinline__ void mma8(float* c, uint32_t a0, uint32_t a1, uint32_t b0) {
  asm volatile("mma.sync.aligned.m16n8k8.row.col.f32.bf16.bf16.f32 {%0,%1,%2,%3},{%4,%5},{%6},{%0,%1,%2,%3};" : "+f"(c[0]), "+f"(c[1]), "+f"(c[2]), "+f"(c[3]) : "r"(a0), "r"(a1), "r"(b0));
}
__device__ __forceinline__ uint4 ldg128(const void* p) { uint4 v; asm volatile("ld.global.nc.v4.b32 {%0,%1,%2,%3},[%4];" : "=r"(v.x), "=r"(v.y), "=r"(v.z), "=r"(v.w) : "l"(p)); return v; }
__device__ __forceinline__ uint4 ldcg128(const void* p) { uint4 v; asm volatile("ld.global.cg.v4.b32 {%0,%1,%2,%3},[%4];" : "=r"(v.x), "=r"(v.y), "=r"(v.z), "=r"(v.w) : "l"(p) : "memory"); return v; }
__device__ __forceinline__ uint32_t ldg32(const void* p) { uint32_t v; asm volatile("ld.global.nc.b32 %0,[%1];" : "=r"(v) : "l"(p)); return v; }
__device__ __forceinline__ uint32_t ldg16(const void* p) { uint16_t v; asm volatile("ld.global.nc.b16 %0,[%1];" : "=h"(v) : "l"(p)); return v; }
__device__ __forceinline__ float bfround(float x) { return __bfloat162float(__float2bfloat16_rn(x)); }
__device__ __forceinline__ void cexp(float er, float f, float j, float& re, float& im) {
  float q = fmaf(f, j, 12582912.f) - 12582912.f;
  float r = fmaf(f, j, -q) * 6.283185307179586f;
  float mg = ex2(er);
  re = mg * __cosf(r); im = mg * __sinf(r);
}
#define CMUL(orr, oi, ar, ai, br, bi) do { float _r = (ar) * (br) - (ai) * (bi); float _i = (ar) * (bi) + (ai) * (br); orr = _r; oi = _i; } while (0)

__device__ __forceinline__ int tile_n0(int n) { return (n >> 1) * 432 + (n & 1) * 224; }

template <int KH>
__device__ __forceinline__ void final_epi(const Params& P, float* acc, const uint32_t* xr, const uint32_t* b2r, uint32_t sb, uint32_t bb, int m, int nt, int wg, int w, int lane) {
  const int tid = wg * 128 + w * 32 + lane;
  mbar_wait_cl(bb + B_XR, 0);
  {
    uint32_t rx = mapa(sb + OFF_X + tid * 16, KH ^ 1), rb = mapa(bb + B_XF, KH ^ 1);
#pragma unroll
    for (int i = 0; i < 10; i++) {
      const float* s = acc + (KH ? 0 : 40) + 4 * i;
      asm volatile("st.async.shared::cluster.mbarrier::complete_tx::bytes.v4.f32 [%0],{%1,%2,%3,%4},[%5];" ::"r"(rx + i * 4096), "f"(s[0]), "f"(s[1]), "f"(s[2]), "f"(s[3]), "r"(rb) : "memory");
    }
  }
  uint32_t sr[20];
  mbar_wait(bb + B_SF, 0);
  {
    uint32_t ch = (uint32_t)((2 * w + ((lane >> 3) & 1)) ^ ((2 * m + wg) & 3) ^ (lane & 7));
    uint32_t a = sb + OFF_S + wg * 10240 + ((lane >> 4) * 8 + (lane & 7)) * 128 + ch * 16;
#pragma unroll
    for (int i = 0; i < 5; i++) ldsm4t(sr + 4 * i, a + i * 2048);
  }
  mbar_wait_cl(bb + B_XF, 0);
  const int g = lane >> 2, t = lane & 3;
  uint32_t* o0 = (uint32_t*)(P.out + (size_t)(m * 128 + wg * 64 + w * 16 + g) * 640 + nt * 160 + KH * 80 + 2 * t);
#pragma unroll
  for (int i = 0; i < 10; i++) {
    float4 pv = lds128f(sb + OFF_X + tid * 16 + i * 4096);
    const float* k = acc + (KH ? 40 : 0) + 4 * i;
    float c0 = blo(b2r[i]), c1 = bhi(b2r[i]);
    float z0 = 0.5f * (k[0] + pv.x + c0), z1 = 0.5f * (k[1] + pv.y + c1), z2 = 0.5f * (k[2] + pv.z + c0), z3 = 0.5f * (k[3] + pv.w + c1);
    float g0 = fmaf(z0, tanh_ap(z0), z0), g1 = fmaf(z1, tanh_ap(z1), z1), g2 = fmaf(z2, tanh_ap(z2), z2), g3 = fmaf(z3, tanh_ap(z3), z3);
    uint32_t s0 = sr[2 * i], s1 = sr[2 * i + 1], x0 = xr[2 * i], x1 = xr[2 * i + 1];
    o0[4 * i] = pack(fmaf(blo(s0), g0, blo(x0)), fmaf(bhi(s0), g1, bhi(x0)));
    o0[4 * i + 8 * 320] = pack(fmaf(blo(s1), g2, blo(x1)), fmaf(bhi(s1), g3, bhi(x1)));
  }
}

template <int PAR>
__device__ __forceinline__ void consumer(const Params& P, uint32_t sb, int m, int nt, int kh, int wid, int lane, unsigned ep, long long tstart) {
  const uint32_t bb = sb + OFF_BAR;
  const int wg = wid >> 2, w = wid & 3, n = kh * 4 + nt, n0 = tile_n0(n);
  constexpr int NT1 = PAR ? 26 : 28;
  {
    float acc[NT1 * 4];
#pragma unroll
    for (int j = 0; j < NT1 * 4; j++) acc[j] = 0.f;
    const CUtensorMap* mb = &P.mw1b[n];
#pragma unroll
    for (int p = 0; p < 20; p++) {
      const int it = p / 2, sa = it % 3, s = (p + 4) % 5;
      if ((p & 1) == 0) mbar_wait(bb + B_FA + 8 * sa, (it / 3) & 1);
      mbar_wait(bb + B_FB + 8 * s, (p / 5) & 1);
      if (p == 0 && threadIdx.x == 0) STAMP(1);
      uint64_t da = mkdesc(sb + OFF_A + sa * 16384 + wg * 8192 + (p & 1) * 64, 1, 64, 1);
      uint64_t db = mkdesc(sb + OFF_B + s * 16384, 256, 64, 1);
      WG_FENCE();
#pragma unroll
      for (int kk = 0; kk < 2; kk++) {
        wg_ss_128(acc, da + kk * 2, db + kk * 128);
        if (PAR) wg_ss_80(acc + 64, da + kk * 2, db + kk * 128 + 512); else wg_ss_96(acc + 64, da + kk * 2, db + kk * 128 + 512);
      }
      WG_COMMIT();
      WG_WAIT(1);
      const int q = p - 1;
      if (q >= 0 && q <= 14) {
        if (elect()) {
          if (atom_inc(bb + B_C1 + 4 * q) == 7) {
            const int sq = (q + 4) % 5;
            uint32_t d = sb + OFF_B + sq * 16384, fb = bb + B_FB + 8 * sq;
            mbar_expect(fb, 16384);
            tma3d(d, &P.mw1a, fb, n0, (q + 5) * 32, 0);
            tma2d(d + 12288, mb, fb, 192, (q + 5) * 32);
            if (q & 1) {
              const int as = (q / 2) % 3;
              mbar_expect(bb + B_FA + 8 * as, 16384);
              tma2d(sb + OFF_A + as * 16384, &P.mx, bb + B_FA + 8 * as, (q / 2 + 3) * 64, m * 128);
            }
          }
        }
        __syncwarp();
      }
      if (q == 15) BAR_ARRIVE(8, 384);
    }
    WG_WAIT(0);
    BAR_ARRIVE(5, 512);
    if (threadIdx.x == 0) STAMP(2);
    BAR_SYNC(7, 384);
    if (wid == 4 && elect()) {
#pragma unroll
      for (int i = 0; i < 4; i++) {
        uint32_t d = sb + OFF_W + i * 12288, fb = bb + B_FW + 8 * i;
        mbar_expect(fb, 12288);
        tma3d(d, &P.mw2a, fb, nt * 160, n0 + 32 * i, 0);
        tma2d(d + 8192, &P.mw2b[nt], fb, 128, n0 + 32 * i);
      }
    }
    __syncwarp();
    const int g = lane >> 2, t = lane & 3;
    float a0, c0, a1, c1;
    {
      uint32_t sa_ = sb + OFF_ST + (wg * 64 + w * 16 + g) * 8;
      a0 = ldsf(sa_); c0 = ldsf(sa_ + 4); a1 = ldsf(sa_ + 64); c1 = ldsf(sa_ + 68);
    }
    const uint32_t cb = sb + OFF_CB + t * 16;
    const uint32_t hst = sb + OFF_HST + (lane >> 4) * 2048 + (wg * 64 + w * 16 + (lane & 15)) * 16;
    const float k0 = 1.5957691216057308f, k1 = 0.2854192648f;
#pragma unroll
    for (int i = 0; i < NT1; i += 2) {
      uint32_t r[4];
#pragma unroll
      for (int u = 0; u < 2; u++) {
        float4 cv = lds128f(cb + (i + u) * 64);
        const float* a = acc + 4 * (i + u);
        float z0 = fmaf(a0, a[0], fmaf(c0, cv.x, cv.y)), z1 = fmaf(a0, a[1], fmaf(c0, cv.z, cv.w));
        float z2 = fmaf(a1, a[2], fmaf(c1, cv.x, cv.y)), z3 = fmaf(a1, a[3], fmaf(c1, cv.z, cv.w));
        float h0 = fmaf(z0, tanh_ap(z0 * fmaf(z0 * z0, k1, k0)), z0), h1 = fmaf(z1, tanh_ap(z1 * fmaf(z1 * z1, k1, k0)), z1);
        float h2 = fmaf(z2, tanh_ap(z2 * fmaf(z2 * z2, k1, k0)), z2), h3 = fmaf(z3, tanh_ap(z3 * fmaf(z3 * z3, k1, k0)), z3);
        r[2 * u] = pack(h0, h1); r[2 * u + 1] = pack(h2, h3);
      }
      stsm4(hst + i * 2048, r[0], r[1], r[2], r[3]);
    }
  }
  FENCE_ASYNC_SH();
  BAR_SYNC(4, 256);
  if (threadIdx.x == 0) { bulk_st(g_H + (size_t)(m * 216 + (n0 >> 3)) * 128, sb + OFF_HST, NT1 * 2048); STAMP(3); }
  __syncwarp();
  uint32_t xr[20], b2r[10];
  {
    const int g = lane >> 2, t = lane & 3;
    const __nv_bfloat16* xp = P.x + (size_t)(m * 128 + wg * 64 + w * 16 + g) * 640 + nt * 160 + kh * 80 + 2 * t;
#pragma unroll
    for (int i = 0; i < 10; i++) { xr[2 * i] = ldg32(xp + 8 * i); xr[2 * i + 1] = ldg32(xp + 8 * i + 8 * 640); b2r[i] = ldg32(P.b2 + nt * 160 + kh * 80 + 2 * t + 8 * i); }
  }
  float acc[80];
#pragma unroll
  for (int j = 0; j < 80; j++) acc[j] = 0.f;
  const int kb1 = tile_n0(n ^ 1), kb2 = tile_n0(n ^ 2), kb3 = tile_n0(n ^ 3);
  asm volatile("barrier.cluster.wait.aligned;" ::: "memory");
  BAR_SYNC(6, 512);
  if (threadIdx.x == 0) STAMP(4);
#pragma unroll
  for (int i = 0; i < 28; i++) {
    const int tau = i / 7, ip = i % 7, ws = i % 4, hs = (i >= 7) ? (i - 7) % 6 : 0;
    const int steps = (((PAR ^ tau) & 1) && ip == 6) ? 1 : 2;
    mbar_wait(bb + B_FW + 8 * ws, (i / 4) & 1);
    if (tau > 0) mbar_wait(bb + B_FH + 8 * hs, ((i - 7) / 6) & 1);
    const uint32_t aoff = (tau == 0) ? OFF_HST + ip * 8192 : OFF_SLOT0 + (hs >> 1 == 2 ? 3 : hs >> 1) * SLOT_SZ + (hs & 1) * 8192;
    uint64_t da = mkdesc(sb + aoff + wg * 1024, 128, 8, 0);
    uint64_t db = mkdesc(sb + OFF_W + ws * 12288, 256, 64, 1);
    WG_FENCE();
#pragma unroll
    for (int kk = 0; kk < steps; kk++) wg_ss_160(acc, da + kk * 256, db + kk * 128);
    WG_COMMIT();
    if (i == 1) {
      if (threadIdx.x == 0) {
        asm volatile("cp.async.bulk.wait_group 0;" ::: "memory");
        FENCE_ASYNC();
        asm volatile("st.release.gpu.global.u32 [%0],%1;" ::"l"(g_flagH + (m * 8 + n) * 8), "r"(ep + 1) : "memory");
        mbar_arrive(bb + B_OD);
        mbar_arrive_cl(mapa(bb + B_XR, kh ^ 1));
        STAMP(5);
      }
      __syncwarp();
    }
    WG_WAIT(1);
    const int q = i - 1;
    if (q >= 0 && q <= 23) {
      if (elect()) {
        if (atom_inc(bb + B_C2 + 4 * q) == 7) {
          const int nx = q + 4, tq = nx / 7;
          const int kc = (tq == 0 ? n0 : tq == 1 ? kb1 : tq == 2 ? kb2 : kb3) + 32 * (nx % 7);
          uint32_t d = sb + OFF_W + (q % 4) * 12288, fb = bb + B_FW + 8 * (q % 4);
          mbar_expect(fb, 12288);
          tma3d(d, &P.mw2a, fb, nt * 160, kc, 0);
          tma2d(d + 8192, &P.mw2b[nt], fb, 128, kc);
          if (q == 6) { mbar_arrive(bb + B_OD); mbar_arrive_cl(mapa(bb + B_XR, kh ^ 1)); }
          if (q >= 7 && q <= 21) mbar_arrive(bb + B_EH + 8 * ((q - 7) % 6));
        }
      }
      __syncwarp();
    }
  }
  WG_WAIT(0);
  if (threadIdx.x == 0) STAMP(6);
  if (kh) final_epi<1>(P, acc, xr, b2r, sb, bb, m, nt, wg, w, lane);
  else final_epi<0>(P, acc, xr, b2r, sb, bb, m, nt, wg, w, lane);
  if (threadIdx.x == 0) { g_ep[blockIdx.x] = ep + 1; STAMP(7); }
}

__device__ __forceinline__ uint32_t kp_idx(int v) {
  int c;
  if (v < 256) c = v & 7;
  else if (v < 512) c = 8 + ((v & 7) >> 1);
  else if (v < 1024) c = 12 + 2 * ((v >> 8) & 1) + ((v & 7) >> 2);
  else c = 16 + ((v - 1024) >> 8);
  return (uint32_t)(c * 36 + ((v >> 3) & 31)) * 4;
}

__device__ __forceinline__ void kgen(uint32_t pl, uint32_t pc, uint32_t pd, uint32_t bt, uint32_t kp, uint32_t kt, int barid, int tid) {
  const int w = tid >> 5, lane = tid & 31, g = lane >> 2, t = lane & 3, hf = w >> 1;
  const uint32_t pt = bt + 12288;
  {
    const float dt = bfround(expf(blo(pd)));
    const float ar = -bfround(expf(blo(pl))) * dt * 1.4426950408889634f;
    const float ai = bhi(pl) * dt * 0.15915494309189535f;
    float wr[8], wi[8], z1r, z1i, z2r, z2i, z4r, z4i, yr, yi, sr_, si_;
    wr[0] = 2.f * dt * blo(pc); wi[0] = 2.f * dt * bhi(pc);
    cexp(ar, ai, 1.f, z1r, z1i);
    cexp(ar * 64.f, ai, 64.f, sr_, si_);
    cexp(ar * 256.f, ai, 256.f, yr, yi);
    sts128f(pt + tid * 16, ar * 8.f, ai * 8.f, sr_, si_);
    CMUL(z2r, z2i, z1r, z1i, z1r, z1i); CMUL(z4r, z4i, z2r, z2i, z2r, z2i);
    CMUL(wr[1], wi[1], wr[0], wi[0], z1r, z1i);
    CMUL(wr[2], wi[2], wr[0], wi[0], z2r, z2i); CMUL(wr[3], wi[3], wr[1], wi[1], z2r, z2i);
#pragma unroll
    for (int i = 0; i < 4; i++) CMUL(wr[4 + i], wi[4 + i], wr[i], wi[i], z4r, z4i);
    const uint32_t rb = bt + (w & 1) * 6144 + hf * 3072 + t * 4;
#define BST(c, re, im) sts32(rb + (c) * 128 + ((g ^ ((c) & 7)) << 4), pack(re, -(im)))
#pragma unroll
    for (int i = 0; i < 8; i++) BST(i, wr[i], wi[i]);
#pragma unroll
    for (int i = 0; i < 4; i++) { CMUL(wr[2 * i], wi[2 * i], wr[2 * i], wi[2 * i], yr, yi); BST(8 + i, wr[2 * i], wi[2 * i]); }
#pragma unroll
    for (int u = 0; u < 2; u++)
#pragma unroll
      for (int i = 0; i < 2; i++) { CMUL(wr[4 * i], wi[4 * i], wr[4 * i], wi[4 * i], yr, yi); BST(12 + 2 * u + i, wr[4 * i], wi[4 * i]); }
#pragma unroll
    for (int i = 0; i < 5; i++) { CMUL(wr[0], wi[0], wr[0], wi[0], yr, yi); BST(16 + i, wr[0], wi[0]); }
#undef BST
  }
  FENCE_ASYNC_SH();
  BAR_SYNC(barid, 128);
  float acc[24];
#pragma unroll
  for (int j = 0; j < 24; j++) acc[j] = 0.f;
  const float jf = (float)((w & 1) * 16 + g);
  const uint64_t db = mkdesc(bt, 1, 64, 1);
#pragma unroll
  for (int s = 0; s < 8; s++) {
    uint32_t a[4];
#pragma unroll
    for (int u = 0; u < 2; u++) {
      float4 pv = lds128f(pt + (hf * 64 + 8 * s + 4 * u + t) * 16);
      float er, ei, fr, fi;
      cexp(pv.x * jf, pv.y, jf, er, ei);
      CMUL(fr, fi, er, ei, pv.z, pv.w);
      a[2 * u] = pack(er, ei); a[2 * u + 1] = pack(fr, fi);
    }
    WG_FENCE();
    wg_rs_48(acc, a[0], a[1], a[2], a[3], db + (s >> 2) * 384 + (s & 3) * 2);
    WG_COMMIT();
  }
  WG_WAIT(0);
  {
    const uint32_t o = kp + hf * 3456 + (2 * t * 36 + (w & 1) * 16 + g) * 4;
#pragma unroll
    for (int i = 0; i < 3; i++) {
      stsf(o + i * 1152, hf ? acc[12 + 4 * i] : acc[4 * i]);
      stsf(o + i * 1152 + 144, hf ? acc[13 + 4 * i] : acc[4 * i + 1]);
      stsf(o + i * 1152 + 32, hf ? acc[14 + 4 * i] : acc[4 * i + 2]);
      stsf(o + i * 1152 + 176, hf ? acc[15 + 4 * i] : acc[4 * i + 3]);
    }
  }
  BAR_SYNC(barid, 128);
#pragma unroll
  for (int e = 0; e < 7; e++) {
    int v; uint32_t dst; bool ok, okh = true;
    if (e < 5) { int l = tid + 128 * e; v = (e < 2) ? l : (int)bfround((float)l); dst = (l + 32) * 4; ok = l <= 541; }
    else if (e == 5) { int mm = 32 + lane; v = 16 * mm + (w == 0 ? 4 : w == 1 ? 12 : w == 2 ? 8 : 16); dst = 2432 + w * 256 + (mm - 18) * 4; ok = mm >= (w == 3 ? 33 : 34); }
    else { int mm = 64 + (tid & 63); v = 16 * mm + 8 + 8 * hf; dst = 3456 + hf * 320 + (mm - 48) * 4; ok = true; okh = mm < 127; }
    if (ok) {
      uint32_t ix = kp + kp_idx(v);
      float kv = ldsf(ix) + ldsf(ix + 3456);
      if (e == 0 && tid == 0) kv += bhi(pd);
      uint32_t hb = pack(kv, kv);
      sts16(kt + dst, hb);
      if (okh) sts16(kt + dst + 6, hb);
    }
  }
}

__device__ __forceinline__ void prep(int ch, uint32_t sl, int i) {
  const uint4* src = g_xnT + ((size_t)i * 640 + ch) * 2;
  uint4 c0 = ldcg128(src), c1 = ldcg128(src + 1), p0 = make_uint4(0, 0, 0, 0), p1 = p0;
  if (i > 0 && i < 96) { p0 = ldcg128(src - 1280); p1 = ldcg128(src - 1279); }
  if (i < 32) sts128(sl + (i >> 3) * UPS + (i & 7) * 16, 0, 0, 0, 0);
  if (i >= 32 && i < 35) sts128(sl + (i == 32 ? S_F3 + 1536 : i == 33 ? S_F5 + 1536 : S_F9 + 1024), 0, 0, 0, 0);
  {
    uint32_t a = sl + (i & 1) * 2 * UPS + 128 + (i >> 1) * 16;
    sts128(a, c0.x, c0.y, c0.z, c0.w); sts128(a + UPS, c1.x, c1.y, c1.z, c1.w);
  }
  if (i < 96) {
    float e[28];
    const uint32_t raw[14] = {p0.z, p0.w, p1.x, p1.y, p1.z, p1.w, c0.x, c0.y, c0.z, c0.w, c1.x, c1.y, c1.z, c1.w};
#pragma unroll
    for (int j = 0; j < 14; j++) { e[2 * j] = blo(raw[j]); e[2 * j + 1] = bhi(raw[j]); }
    float G[22], T[19], F[16];
#pragma unroll
    for (int j = 0; j < 22; j++) G[j] = e[j + 3] + e[j + 2];
#pragma unroll
    for (int j = 0; j < 19; j++) T[j] = G[j + 3] + e[j + 4];
#define ST16(a0, a1, V, o) do { sts128(a0, pack(V[o], V[o + 1]), pack(V[o + 2], V[o + 3]), pack(V[o + 4], V[o + 5]), pack(V[o + 6], V[o + 7])); \
                                sts128(a1, pack(V[o + 8], V[o + 9]), pack(V[o + 10], V[o + 11]), pack(V[o + 12], V[o + 13]), pack(V[o + 14], V[o + 15])); } while (0)
    ST16(sl + S_F3 + i * 16, sl + S_F3 + 1552 + i * 16, T, 3);
#pragma unroll
    for (int j = 0; j < 16; j++) F[j] = T[j] + G[j];
    ST16(sl + S_F5 + i * 16, sl + S_F5 + 1552 + i * 16, F, 0);
    if (i < 64) {
      uint32_t ga = sl + S_G + (i & 1) * 2 * GPS + (i >> 1) * 16;
      ST16(ga, ga + GPS, G, 6);
#pragma unroll
      for (int j = 0; j < 16; j++) F[j] += e[j + 7] + e[j + 1];
      ST16(sl + S_F7 + i * 16, sl + S_F7 + 1024 + i * 16, F, 0);
#pragma unroll
      for (int j = 0; j < 16; j++) F[j] += e[j + 8] + e[j];
      ST16(sl + S_F9 + i * 16, sl + S_F9 + 1040 + i * 16, F, 0);
    }
#undef ST16
  }
}

__device__ __forceinline__ void conv_near(float* acc, uint32_t sl, uint32_t kt, int w, int lane) {
  const int g = lane >> 2, t = lane & 3;
  const uint32_t pa = kt + (32 + 16 * ((w & 1) + 18 * (w >> 1) - 1) + g - 2 * t) * 4;
  const uint64_t db = mkdesc(sl + 128, UPS / 16, 8, 0);
  uint32_t prev = lds32(pa - 32);
#pragma unroll
  for (int b = 0; b < 3; b++) {
    uint32_t mid[6], hi[6];
    if (b == 2) WG_WAIT(1);
#pragma unroll
    for (int u = 0; u < 6; u++) { mid[u] = lds32(pa + (b * 6 + u) * 64); hi[u] = lds32(pa + (b * 6 + u) * 64 + 32); }
    WG_FENCE();
#pragma unroll
    for (int u = 0; u < 6; u++) {
      const int a = b * 6 + u - 1;
      const int pl = (a & 1) ? 2 : 0, ro = -((a + 1) >> 1);
      wg_rs_64(acc, mid[u], hi[u], u ? hi[u - 1] : prev, mid[u], db + (pl * (int)(UPS / 16) + ro));
    }
    WG_COMMIT();
    prev = hi[5];
  }
  WG_WAIT(0);
}

template <int NB, int T0>
__device__ __forceinline__ void conv_class(float* acc, uint32_t fa, uint32_t ta) {
  constexpr int NX = (NB == 6) ? 3 : 4;
  uint32_t b[2 * NX];
#pragma unroll
  for (int i = 0; i < 2 * NX; i++) b[i] = lds32(ta + i * 32);
#pragma unroll
  for (int c = 0; c < NB; c++) {
    uint32_t a[4];
    ldsm4t(a, fa + c * 256);
#pragma unroll
    for (int x = 0; x < NX; x++)
      if (c + x < NB) mma16(acc + 4 * (T0 + c + x), a, b[2 * x + 1], b[2 * x]);
  }
}

__device__ __forceinline__ void conv_far(float* acc, uint32_t sl, uint32_t kt, int w, int lane) {
  const int g = lane >> 2, t = lane & 3, w2 = w & 1, hb = (lane >> 3) & 1;
  const uint32_t ro = sl + ((lane >> 4) * 8 + (lane & 7)) * 16;
  const uint32_t tb = kt + (w2 + 2 * (g - t)) * 4;
  if (w >> 1) {
    conv_class<6, 1>(acc, ro + S_F3 + (hb ? 1552 : 0), tb + 2432 + (26 - 18) * 4);
    conv_class<6, 1>(acc, ro + S_F3 + (hb ? 0 : 1536), tb + 2432 + 256 + (26 - 18) * 4);
    conv_class<6, 1>(acc, ro + S_F5 + (hb ? 1552 : 0), tb + 2432 + 512 + (26 - 18) * 4);
  } else {
    conv_class<6, 2>(acc, ro + S_F5 + (hb ? 0 : 1536), tb + 2432 + 768 + (24 - 18) * 4);
    conv_class<4, 4>(acc, ro + S_F7 + (hb ? 1024 : 0), tb + 3456 + (56 - 48) * 4);
    conv_class<4, 4>(acc, ro + S_F9 + (hb ? 0 : 1024), tb + 3456 + 320 + (56 - 48) * 4);
    uint32_t kv = lds32(kt + 2432 + 768 + (63 - 18) * 4) & 0xffffu;
    uint32_t d = (g == 2 * t) ? kv : (g == 2 * t + 1) ? kv << 16 : 0u;
#pragma unroll
    for (int c = 0; c < 2; c++) {
      uint32_t a[4];
      ldsm4t(a, ro + S_G + (2 * w2 + hb) * GPS + c * 256);
      mma8(acc + 4 * (4 + 2 * c), a[0], a[1], d);
      mma8(acc + 4 * (5 + 2 * c), a[2], a[3], d);
    }
  }
}

__device__ __forceinline__ void aux(const Params& P, uint32_t sb, int m, int nt, int kh, int wid, int lane, unsigned ep, long long tstart) {
  const uint32_t bb = sb + OFF_BAR;
  const int n = kh * 4 + nt, n0 = tile_n0(n), par = n & 1, aw = wid - 8, sel = aw >> 2, w = aw & 3, tid = w * 32 + lane, at = aw * 32 + lane;
  const int ch0 = blockIdx.x * 5, tb = m * 8 + n;
  uint4 xv[5], wv[5];
  {
    const __nv_bfloat16* xp = P.x + (size_t)(tb * 16 + 2 * aw + (lane >> 4)) * 640 + (lane & 15) * 8;
#pragma unroll
    for (int i = 0; i < 5; i++) xv[i] = ldg128(xp + i * 128);
    const bool wok = lane < (par ? 26 : 28);
    const __nv_bfloat16* wp = P.w1 + (size_t)(m * 40 + aw * 5) * 1728 + n0 + (wok ? lane : 0) * 8;
#pragma unroll
    for (int i = 0; i < 5; i++) wv[i] = ldg128(wp + i * 1728);
  }
  uint32_t pl[3], pc[3], pd[3];
#pragma unroll
  for (int r = 0; r < 3; r++) {
    int c = ch0 + ((r == 2) ? 4 : 2 * r + sel);
    pl[r] = ldg16(P.logA + c * 128 + tid) | (ldg16(P.Aim + c * 128 + tid) << 16);
    pc[r] = ldg16(P.Cre + c * 128 + tid) | (ldg16(P.Cim + c * 128 + tid) << 16);
    pd[r] = ldg16(P.logdt + c) | (ldg16(P.Dsk + c) << 16);
  }
#pragma unroll
  for (int i = 0; i < 5; i++) sts128(sb + OFF_KT + (i * 256 + at) * 16, 0, 0, 0, 0);
  const uint32_t stg = sb + OFF_SLOT0, csp = stg + 20736;
  {
    float v[40];
#pragma unroll
    for (int i = 0; i < 5; i++) {
      v[8 * i] = blo(xv[i].x); v[8 * i + 1] = bhi(xv[i].x); v[8 * i + 2] = blo(xv[i].y); v[8 * i + 3] = bhi(xv[i].y);
      v[8 * i + 4] = blo(xv[i].z); v[8 * i + 5] = bhi(xv[i].z); v[8 * i + 6] = blo(xv[i].w); v[8 * i + 7] = bhi(xv[i].w);
    }
    float s = 0.f;
#pragma unroll
    for (int i = 0; i < 40; i++) s += v[i];
#pragma unroll
    for (int o = 8; o; o >>= 1) s += __shfl_xor_sync(0xffffffffu, s, o);
    const float mean = s * (1.f / 640.f);
    float q = 0.f;
#pragma unroll
    for (int i = 0; i < 40; i++) { v[i] -= mean; q = fmaf(v[i], v[i], q); }
#pragma unroll
    for (int o = 8; o; o >>= 1) q += __shfl_xor_sync(0xffffffffu, q, o);
    const float var = q * (1.f / 640.f);
    const float r1 = rsqrtf(var + 1e-5f), r2 = rsqrtf(var * r1 * r1 + 1e-5f);
    const int tk = 2 * aw + (lane >> 4);
    if ((lane & 15) == 0) { float a = 0.5f * r1 * r2; g_stats[tb * 16 + tk] = make_float2(a, -mean * a); }
    const uint32_t ra = stg + (((tk >> 1) & 1) * 8 + (tk >> 2) * 2 + (tk & 1)) * 1296 + (lane & 15) * 16;
#pragma unroll
    for (int i = 0; i < 5; i++)
      sts128(ra + i * 256, pack(v[8 * i] * r1, v[8 * i + 1] * r1), pack(v[8 * i + 2] * r1, v[8 * i + 3] * r1), pack(v[8 * i + 4] * r1, v[8 * i + 5] * r1), pack(v[8 * i + 6] * r1, v[8 * i + 7] * r1));
    float cs[8];
#pragma unroll
    for (int j = 0; j < 8; j++) cs[j] = 0.f;
#pragma unroll
    for (int i = 0; i < 5; i++) {
      cs[0] += blo(wv[i].x); cs[1] += bhi(wv[i].x); cs[2] += blo(wv[i].y); cs[3] += bhi(wv[i].y);
      cs[4] += blo(wv[i].z); cs[5] += bhi(wv[i].z); cs[6] += blo(wv[i].w); cs[7] += bhi(wv[i].w);
    }
    if (lane < 28) { sts128f(csp + aw * 896 + lane * 32, cs[0], cs[1], cs[2], cs[3]); sts128f(csp + aw * 896 + lane * 32 + 16, cs[4], cs[5], cs[6], cs[7]); }
  }
  BAR_SYNC(1, 256);
  {
    const uint32_t la = stg + (lane & 15) * 1296 + (aw * 10 + (lane >> 4)) * 16;
    uint2* dst = (uint2*)g_xnT + ((size_t)tb * 640 + aw * 80) * 4 + lane;
#pragma unroll
    for (int i = 0; i < 5; i++) {
      uint32_t r[4];
      ldsm4t(r, la + i * 32);
      dst[i * 64] = make_uint2(r[0], r[1]); dst[i * 64 + 32] = make_uint2(r[2], r[3]);
    }
    if (at < (par ? 208 : 224)) {
      float s = 0.f;
#pragma unroll
      for (int i = 0; i < 8; i++) s += ldsf(csp + i * 896 + at * 4);
      g_csp[m * 1728 + n0 + at] = s;
    }
  }
  BAR_SYNC(1, 256);
  if (at == 224) {
    __threadfence();
    asm volatile("red.relaxed.gpu.global.add.u32 [%0],1;" ::"l"(g_cnt_ln) : "memory");
    asm volatile("cp.async.bulk.prefetch.L2.global [%0],17280;" ::"l"((const char*)P.w2 + blockIdx.x * 17280) : "memory");
    STAMP(8);
  }
  __syncwarp();
  const int wbar = 2 + sel;
  const uint32_t slA = sb + OFF_SLOT0 + sel * SLOT_SZ, slB = slA + 2 * SLOT_SZ;
#pragma unroll 1
  for (int r = 0; r < 3 - sel; r++) {
    uint32_t a = r == 0 ? pl[0] : r == 1 ? pl[1] : pl[2], b = r == 0 ? pc[0] : r == 1 ? pc[1] : pc[2], c = r == 0 ? pd[0] : r == 1 ? pd[1] : pd[2];
    kgen(a, b, c, slB, slA, sb + OFF_KT + (2 * r + sel) * 4096, wbar, tid);
  }
  if (tid == 0) { STAMP(9 + sel); poll_ge(g_cnt_ln, (ep + 1) * 128); STAMP(11 + sel); }
  BAR_SYNC(wbar, 128);
  if (sel) {
#pragma unroll
    for (int h = 0; h < 2; h++) {
      int c = tid + 128 * h;
      if (c < (par ? 208 : 224)) {
        float s = 0.f;
#pragma unroll
        for (int i = 0; i < 16; i++) s += __ldcg(g_csp + i * 1728 + n0 + c);
        stsf(sb + OFF_CB + c * 8, s); stsf(sb + OFF_CB + c * 8 + 4, 0.5f * blo(ldg16(P.b1 + n0 + c)));
      }
    }
    float2 st = __ldcg(g_stats + m * 128 + tid);
    stsf(sb + OFF_ST + tid * 8, st.x); stsf(sb + OFF_ST + tid * 8 + 4, st.y);
    BAR_ARRIVE(7, 384);
  }
  const int pi = tid ^ (sel ? 96 : 0);
#pragma unroll 1
  for (int r = 0; r < 2 + sel; r++) {
    if (r == 2) BAR_SYNC(8, 384);
    prep(ch0 + (r == 2 ? 4 : 2 * r + sel), r == 0 ? slA : r == 1 ? slB : sb + OFF_SLOT4, pi);
  }
  FENCE_ASYNC_SH();
  BAR_SYNC(wbar, 128);
  if (tid == 0) STAMP(13 + sel);
  asm volatile("barrier.cluster.wait.aligned;" ::: "memory");
  const int g = lane >> 2, t = lane & 3, w2 = w & 1;
#pragma unroll 1
  for (int r = 0; r < 3 - sel; r++) {
    const uint32_t sl = r == 0 ? slA : r == 1 ? slB : sb + OFF_SLOT4, kt = sb + OFF_KT + (2 * r + sel) * 4096;
    float acc[32];
#pragma unroll
    for (int j = 0; j < 32; j++) acc[j] = 0.f;
#pragma unroll 1
    for (int st = 0; st < 2; st++) {
      if ((st == 0) == (r == 0)) {
        conv_near(acc, sl, kt, w, lane);
      } else {
        if (r == 0) { if (tid == 0) STAMP(15 + sel); BAR_SYNC(5, 512); }
        conv_far(acc, sl, kt, w, lane);
        if (r == 2 - sel) BAR_ARRIVE(6, 512);
      }
    }
    BAR_SYNC(wbar, 128);
    const uint32_t rd = sl + S_RED + (2 * t * 36 + w2 * 16 + g) * 4;
    if (w >> 1) {
#pragma unroll
      for (int i = 0; i < 7; i++) { stsf(rd + i * 1152, acc[4 * i]); stsf(rd + i * 1152 + 144, acc[4 * i + 1]); stsf(rd + i * 1152 + 32, acc[4 * i + 2]); stsf(rd + i * 1152 + 176, acc[4 * i + 3]); }
    }
    BAR_SYNC(wbar, 128);
    if (!(w >> 1)) {
#pragma unroll
      for (int i = 1; i < 8; i++) {
        float v0 = ldsf(rd + i * 1152 - 1296), v2 = ldsf(rd + i * 1152 - 1296 + 32);
        if (i == 1 && t == 0) { v0 = 0.f; v2 = 0.f; }
        acc[4 * i] += v0; acc[4 * i + 2] += v2;
        acc[4 * i + 1] += ldsf(rd + i * 1152 - 1152); acc[4 * i + 3] += ldsf(rd + i * 1152 - 1152 + 32);
      }
      const uint32_t c = 4 * ((lane >> 4) * 8 + (lane & 7)) + 2 * w2 + ((lane >> 3) & 1);
      const uint32_t oa = sl + ((c ^ ((c >> 3) & 3)) << 4);
#pragma unroll
      for (int i = 0; i < 8; i += 2)
        stsm4t(oa + i * 512, pack(acc[4 * i], acc[4 * i + 1]), pack(acc[4 * i + 2], acc[4 * i + 3]), pack(acc[4 * i + 4], acc[4 * i + 5]), pack(acc[4 * i + 6], acc[4 * i + 7]));
      FENCE_ASYNC_SH();
      BAR_SYNC(10 + sel, 64);
      if (tid == 0) {
        if (r == 1 && !sel) { asm volatile("cp.async.bulk.wait_group.read 0;" ::: "memory"); mbar_arrive(bb + B_S0); }
        bulk_st(g_sT + (size_t)(ch0 + 2 * r + sel) * 256, sl, 4096);
        STAMP(17 + 2 * r + sel);
      }
      __syncwarp();
    }
  }
  if (tid == 0) {
    asm volatile("cp.async.bulk.wait_group 0;" ::: "memory");
    FENCE_ASYNC();
    asm volatile("red.release.gpu.global.add.u32 [%0],%1;" ::"l"(g_cnt_s + (blockIdx.x >> 4) * 32), "r"(3 - sel) : "memory");
    STAMP(22 + sel);
  }
  __syncwarp();
  if (aw == 4) {
    if (elect()) {
      mbar_wait(bb + B_S0, 0);
      FENCE_ASYNC();
#pragma unroll 1
      for (int tau = 1; tau < 4; tau++) {
        const int nn = n ^ tau;
        poll_ge(g_flagH + (m * 8 + nn) * 8, ep + 1);
        FENCE_ASYNC();
        const uint4* src = g_H + (size_t)(m * 216 + (tile_n0(nn) >> 3)) * 128;
#pragma unroll 1
        for (int ip = 0; ip < 7; ip++) {
          const int j = (tau - 1) * 7 + ip, hs = j % 6;
          if (j >= 6) mbar_wait(bb + B_EH + 8 * hs, (j / 6 - 1) & 1);
          const uint32_t bytes = ((nn & 1) && ip == 6) ? 4096 : 8192;
          mbar_expect(bb + B_FH + 8 * hs, bytes);
          bulk_ld(sb + OFF_SLOT0 + (hs >> 1 == 2 ? 3 : hs >> 1) * SLOT_SZ + (hs & 1) * 8192, src + ip * 512, bytes, bb + B_FH + 8 * hs);
        }
      }
      STAMP(24);
    }
  } else if (aw == 5) {
    if (elect()) {
      mbar_wait(bb + B_OD, 0);
      poll_ge(g_cnt_s + (2 * nt + kh) * 32, (ep + 1) * 80);
      FENCE_ASYNC();
      mbar_expect(bb + B_SF, 20480);
      tma2d(sb + OFF_S, &P.ms, bb + B_SF, m * 128, nt * 160 + kh * 80);
      tma2d(sb + OFF_S + 10240, &P.ms, bb + B_SF, m * 128 + 64, nt * 160 + kh * 80);
      STAMP(25);
    }
  }
}

__global__ void __cluster_dims__(2, 1, 1) __launch_bounds__(512, 1) fused_kernel(const __grid_constant__ Params P) {
  extern __shared__ __align__(1024) unsigned char smem[];
  long long tstart = 0;
  uint32_t sb = (uint32_t)__cvta_generic_to_shared(smem);
  asm volatile("mov.u32 %0,%0;" : "+r"(sb));
  const uint32_t bb = sb + OFF_BAR;
  const int wid = __shfl_sync(0xffffffffu, threadIdx.x >> 5, 0), lane = threadIdx.x & 31;
  const int kh = blockIdx.x & 1, p = blockIdx.x >> 1;
  const int nt = (p >> 2) & 3, m = (p >> 4) * 4 + (p & 3);
  const unsigned ep = __ldcg(g_ep + blockIdx.x);
  if (wid == 0) {
    if (elect()) {
      if (sb & 1023) __trap();
#pragma unroll
      for (int i = 0; i < 24; i++) mbar_init(bb + 8 * i, 1);
      mbar_init(bb + B_SF, 1); mbar_init(bb + B_XF, 1); mbar_init(bb + B_XR, 2); mbar_init(bb + B_S0, 1); mbar_init(bb + B_OD, 2);
      asm volatile("fence.mbarrier_init.release.cluster;" ::: "memory");
      FENCE_ASYNC_SH();
      const int n = kh * 4 + nt, n0 = tile_n0(n);
#pragma unroll
      for (int q = 0; q < 5; q++) {
        if ((q & 1) == 0) { mbar_expect(bb + B_FA + 8 * (q / 2), 16384); tma2d(sb + OFF_A + (q / 2) * 16384, &P.mx, bb + B_FA + 8 * (q / 2), q * 32, m * 128); }
        const int s = (q + 4) % 5;
        uint32_t d = sb + OFF_B + s * 16384, fb = bb + B_FB + 8 * s;
        mbar_expect(fb, 16384);
        tma3d(d, &P.mw1a, fb, n0, q * 32, 0);
        tma2d(d + 12288, &P.mw1b[n], fb, 192, q * 32);
      }
      mbar_expect(bb + B_XF, 40960);
    }
    __syncwarp();
  } else if (wid == 1) {
    sts32(bb + B_C1 + lane * 4, 0); sts32(bb + B_C1 + 128 + lane * 4, 0);
  }
  if (wid < 8) {
    BAR_SYNC(4, 256);
    asm volatile("barrier.cluster.arrive.release.aligned;" ::: "memory");
    asm volatile("setmaxnreg.inc.sync.aligned.u32 144;");
    if (nt & 1) consumer<1>(P, sb, m, nt, kh, wid, lane, ep, tstart);
    else consumer<0>(P, sb, m, nt, kh, wid, lane, ep, tstart);
  } else {
    asm volatile("setmaxnreg.dec.sync.aligned.u32 112;");
    asm volatile("barrier.cluster.arrive.relaxed.aligned;" ::: "memory");
    aux(P, sb, m, nt, kh, wid, lane, ep, tstart);
  }
}

typedef CUresult (*EncFn)(CUtensorMap*, CUtensorMapDataType, cuuint32_t, void*, const cuuint64_t*, const cuuint64_t*, const cuuint32_t*, const cuuint32_t*, CUtensorMapInterleave, CUtensorMapSwizzle, CUtensorMapL2promotion, CUtensorMapFloatOOBfill);
static void mk(EncFn enc, CUtensorMap* tm, const void* p, int rank, cuuint64_t d0, cuuint64_t d1, cuuint64_t d2, cuuint64_t s1, cuuint64_t s2, cuuint32_t b0, cuuint32_t b1, cuuint32_t b2) {
  cuuint64_t gd[3] = {d0, d1, d2}, gs[2] = {s1, s2};
  cuuint32_t bd[3] = {b0, b1, b2}, es[3] = {1, 1, 1};
  enc(tm, CU_TENSOR_MAP_DATA_TYPE_BFLOAT16, rank, (void*)p, gd, gs, bd, es, CU_TENSOR_MAP_INTERLEAVE_NONE, CU_TENSOR_MAP_SWIZZLE_128B, CU_TENSOR_MAP_L2_PROMOTION_L2_128B, CU_TENSOR_MAP_FLOAT_OOB_FILL_NONE);
}

extern "C" void kernel_launch(void* const* d_in, const int* in_sizes, int n_in, void* d_out, int out_size) {
  typedef const __nv_bfloat16* bp;
  Params P;
  P.x = (bp)d_in[0]; P.logA = (bp)d_in[1]; P.Aim = (bp)d_in[2]; P.Cre = (bp)d_in[3]; P.Cim = (bp)d_in[4]; P.logdt = (bp)d_in[5]; P.Dsk = (bp)d_in[6];
  P.w1 = (bp)d_in[8]; P.b1 = (bp)d_in[9]; P.w2 = (bp)d_in[10]; P.b2 = (bp)d_in[11]; P.out = (__nv_bfloat16*)d_out;
  void* fn = nullptr; cudaDriverEntryPointQueryResult qr;
  cudaGetDriverEntryPoint("cuTensorMapEncodeTiled", &fn, cudaEnableDefault, &qr);
  EncFn enc = (EncFn)fn;
  void* sT = nullptr; cudaGetSymbolAddress(&sT, g_sT);
  mk(enc, &P.mx, P.x, 2, 640, 2048, 1, 1280, 0, 64, 128, 1);
  mk(enc, &P.mw1a, P.w1, 3, 1728 - 128, 640, 3, 3456, 128, 64, 32, 3);
  for (int n = 0; n < 8; n++) mk(enc, &P.mw1b[n], P.w1 + (n >> 1) * 432 + (n & 1) * 224, 2, (n & 1) ? 208 : 224, 640, 1, 3456, 0, 64, 32, 1);
  mk(enc, &P.mw2a, P.w2, 3, 640 - 64, 1728, 2, 1280, 128, 64, 32, 2);
  for (int n = 0; n < 4; n++) mk(enc, &P.mw2b[n], P.w2 + n * 160, 2, 160, 1728, 1, 1280, 0, 64, 32, 1);
  mk(enc, &P.ms, sT, 2, 2048, 640, 1, 4096, 0, 64, 80, 1);
  cudaFuncSetAttribute(fused_kernel, cudaFuncAttributeMaxDynamicSharedMemorySize, SMEM_BYTES);
  fused_kernel<<<128, 512, SMEM_BYTES, cudaStreamPerThread>>>(P);
}
```

```cpp
#include <cuda_runtime.h>
#include <cuda_bf16.h>
#include <cuda.h>
#include <stdint.h>

__device__ __forceinline__ void wg_ss_160(float* d, uint64_t da, uint64_t db, uint32_t sc){
  asm volatile("{.reg .pred p; setp.ne.b32 p,%82,0; wgmma.mma_async.sync.aligned.m64n160k16.f32.bf16.bf16 {%0,%1,%2,%3,%4,%5,%6,%7,%8,%9,%10,%11,%12,%13,%14,%15,%16,%17,%18,%19,%20,%21,%22,%23,%24,%25,%26,%27,%28,%29,%30,%31,%32,%33,%34,%35,%36,%37,%38,%39,%40,%41,%42,%43,%44,%45,%46,%47,%48,%49,%50,%51,%52,%53,%54,%55,%56,%57,%58,%59,%60,%61,%62,%63,%64,%65,%66,%67,%68,%69,%70,%71,%72,%73,%74,%75,%76,%77,%78,%79},%80,%81,p,1,1,0,1;}"
    :"+f"(d[0]),"+f"(d[1]),"+f"(d[2]),"+f"(d[3]),"+f"(d[4]),"+f"(d[5]),"+f"(d[6]),"+f"(d[7]),"+f"(d[8]),"+f"(d[9]),"+f"(d[10]),"+f"(d[11]),"+f"(d[12]),"+f"(d[13]),"+f"(d[14]),"+f"(d[15]),"+f"(d[16]),"+f"(d[17]),"+f"(d[18]),"+f"(d[19]),"+f"(d[20]),"+f"(d[21]),"+f"(d[22]),"+f"(d[23]),"+f"(d[24]),"+f"(d[25]),"+f"(d[26]),"+f"(d[27]),"+f"(d[28]),"+f"(d[29]),"+f"(d[30]),"+f"(d[31]),"+f"(d[32]),"+f"(d[33]),"+f"(d[34]),"+f"(d[35]),"+f"(d[36]),"+f"(d[37]),"+f"(d[38]),"+f"(d[39]),"+f"(d[40]),"+f"(d[41]),"+f"(d[42]),"+f"(d[43]),"+f"(d[44]),"+f"(d[45]),"+f"(d[46]),"+f"(d[47]),"+f"(d[48]),"+f"(d[49]),"+f"(d[50]),"+f"(d[51]),"+f"(d[52]),"+f"(d[53]),"+f"(d[54]),"+f"(d[55]),"+f"(d[56]),"+f"(d[57]),"+f"(d[58]),"+f"(d[59]),"+f"(d[60]),"+f"(d[61]),"+f"(d[62]),"+f"(d[63]),"+f"(d[64]),"+f"(d[65]),"+f"(d[66]),"+f"(d[67]),"+f"(d[68]),"+f"(d[69]),"+f"(d[70]),"+f"(d[71]),"+f"(d[72]),"+f"(d[73]),"+f"(d[74]),"+f"(d[75]),"+f"(d[76]),"+f"(d[77]),"+f"(d[78]),"+f"(d[79])
    :"l"(da),"l"(db),"r"(sc));
}
__device__ __forceinline__ void wg_rs_128(float* d, uint32_t a0, uint32_t a1, uint32_t a2, uint32_t a3, uint64_t db, uint32_t sc){
  asm volatile("{.reg .pred p; setp.ne.b32 p,%69,0; wgmma.mma_async.sync.aligned.m64n128k16.f32.bf16.bf16 {%0,%1,%2,%3,%4,%5,%6,%7,%8,%9,%10,%11,%12,%13,%14,%15,%16,%17,%18,%19,%20,%21,%22,%23,%24,%25,%26,%27,%28,%29,%30,%31,%32,%33,%34,%35,%36,%37,%38,%39,%40,%41,%42,%43,%44,%45,%46,%47,%48,%49,%50,%51,%52,%53,%54,%55,%56,%57,%58,%59,%60,%61,%62,%63},{%64,%65,%66,%67},%68,p,1,1,1;}"
    :"+f"(d[0]),"+f"(d[1]),"+f"(d[2]),"+f"(d[3]),"+f"(d[4]),"+f"(d[5]),"+f"(d[6]),"+f"(d[7]),"+f"(d[8]),"+f"(d[9]),"+f"(d[10]),"+f"(d[11]),"+f"(d[12]),"+f"(d[13]),"+f"(d[14]),"+f"(d[15]),"+f"(d[16]),"+f"(d[17]),"+f"(d[18]),"+f"(d[19]),"+f"(d[20]),"+f"(d[21]),"+f"(d[22]),"+f"(d[23]),"+f"(d[24]),"+f"(d[25]),"+f"(d[26]),"+f"(d[27]),"+f"(d[28]),"+f"(d[29]),"+f"(d[30]),"+f"(d[31]),"+f"(d[32]),"+f"(d[33]),"+f"(d[34]),"+f"(d[35]),"+f"(d[36]),"+f"(d[37]),"+f"(d[38]),"+f"(d[39]),"+f"(d[40]),"+f"(d[41]),"+f"(d[42]),"+f"(d[43]),"+f"(d[44]),"+f"(d[45]),"+f"(d[46]),"+f"(d[47]),"+f"(d[48]),"+f"(d[49]),"+f"(d[50]),"+f"(d[51]),"+f"(d[52]),"+f"(d[53]),"+f"(d[54]),"+f"(d[55]),"+f"(d[56]),"+f"(d[57]),"+f"(d[58]),"+f"(d[59]),"+f"(d[60]),"+f"(d[61]),"+f"(d[62]),"+f"(d[63])
    :"r"(a0),"r"(a1),"r"(a2),"r"(a3),"l"(db),"r"(sc));
}
__device__ __forceinline__ void wg_rs_96(float* d, uint32_t a0, uint32_t a1, uint32_t a2, uint32_t a3, uint64_t db, uint32_t sc){
  asm volatile("{.reg .pred p; setp.ne.b32 p,%53,0; wgmma.mma_async.sync.aligned.m64n96k16.f32.bf16.bf16 {%0,%1,%2,%3,%4,%5,%6,%7,%8,%9,%10,%11,%12,%13,%14,%15,%16,%17,%18,%19,%20,%21,%22,%23,%24,%25,%26,%27,%28,%29,%30,%31,%32,%33,%34,%35,%36,%37,%38,%39,%40,%41,%42,%43,%44,%45,%46,%47},{%48,%49,%50,%51},%52,p,1,1,1;}"
    :"+f"(d[0]),"+f"(d[1]),"+f"(d[2]),"+f"(d[3]),"+f"(d[4]),"+f"(d[5]),"+f"(d[6]),"+f"(d[7]),"+f"(d[8]),"+f"(d[9]),"+f"(d[10]),"+f"(d[11]),"+f"(d[12]),"+f"(d[13]),"+f"(d[14]),"+f"(d[15]),"+f"(d[16]),"+f"(d[17]),"+f"(d[18]),"+f"(d[19]),"+f"(d[20]),"+f"(d[21]),"+f"(d[22]),"+f"(d[23]),"+f"(d[24]),"+f"(d[25]),"+f"(d[26]),"+f"(d[27]),"+f"(d[28]),"+f"(d[29]),"+f"(d[30]),"+f"(d[31]),"+f"(d[32]),"+f"(d[33]),"+f"(d[34]),"+f"(d[35]),"+f"(d[36]),"+f"(d[37]),"+f"(d[38]),"+f"(d[39]),"+f"(d[40]),"+f"(d[41]),"+f"(d[42]),"+f"(d[43]),"+f"(d[44]),"+f"(d[45]),"+f"(d[46]),"+f"(d[47])
    :"r"(a0),"r"(a1),"r"(a2),"r"(a3),"l"(db),"r"(sc));
}
__device__ __forceinline__ void wg_ss_48(float* d, uint64_t da, uint64_t db, uint32_t sc){
  asm volatile("{.reg .pred p; setp.ne.b32 p,%26,0; wgmma.mma_async.sync.aligned.m64n48k16.f32.bf16.bf16 {%0,%1,%2,%3,%4,%5,%6,%7,%8,%9,%10,%11,%12,%13,%14,%15,%16,%17,%18,%19,%20,%21,%22,%23},%24,%25,p,1,1,1,1;}"
    :"+f"(d[0]),"+f"(d[1]),"+f"(d[2]),"+f"(d[3]),"+f"(d[4]),"+f"(d[5]),"+f"(d[6]),"+f"(d[7]),"+f"(d[8]),"+f"(d[9]),"+f"(d[10]),"+f"(d[11]),"+f"(d[12]),"+f"(d[13]),"+f"(d[14]),"+f"(d[15]),"+f"(d[16]),"+f"(d[17]),"+f"(d[18]),"+f"(d[19]),"+f"(d[20]),"+f"(d[21]),"+f"(d[22]),"+f"(d[23])
    :"l"(da),"l"(db),"r"(sc));
}
__device__ __forceinline__ void wg_rs_64(float* d, uint32_t a0, uint32_t a1, uint32_t a2, uint32_t a3, uint64_t db, uint32_t sc){
  asm volatile("{.reg .pred p; setp.ne.b32 p,%37,0; wgmma.mma_async.sync.aligned.m64n64k16.f32.bf16.bf16 {%0,%1,%2,%3,%4,%5,%6,%7,%8,%9,%10,%11,%12,%13,%14,%15,%16,%17,%18,%19,%20,%21,%22,%23,%24,%25,%26,%27,%28,%29,%30,%31},{%32,%33,%34,%35},%36,p,1,1,0;}"
    :"+f"(d[0]),"+f"(d[1]),"+f"(d[2]),"+f"(d[3]),"+f"(d[4]),"+f"(d[5]),"+f"(d[6]),"+f"(d[7]),"+f"(d[8]),"+f"(d[9]),"+f"(d[10]),"+f"(d[11]),"+f"(d[12]),"+f"(d[13]),"+f"(d[14]),"+f"(d[15]),"+f"(d[16]),"+f"(d[17]),"+f"(d[18]),"+f"(d[19]),"+f"(d[20]),"+f"(d[21]),"+f"(d[22]),"+f"(d[23]),"+f"(d[24]),"+f"(d[25]),"+f"(d[26]),"+f"(d[27]),"+f"(d[28]),"+f"(d[29]),"+f"(d[30]),"+f"(d[31])
    :"r"(a0),"r"(a1),"r"(a2),"r"(a3),"l"(db),"r"(sc));
}
__device__ __forceinline__ void wg_rs_32(float* d, uint32_t a0, uint32_t a1, uint32_t a2, uint32_t a3, uint64_t db, uint32_t sc){
  asm volatile("{.reg .pred p; setp.ne.b32 p,%21,0; wgmma.mma_async.sync.aligned.m64n32k16.f32.bf16.bf16 {%0,%1,%2,%3,%4,%5,%6,%7,%8,%9,%10,%11,%12,%13,%14,%15},{%16,%17,%18,%19},%20,p,1,1,1;}"
    :"+f"(d[0]),"+f"(d[1]),"+f"(d[2]),"+f"(d[3]),"+f"(d[4]),"+f"(d[5]),"+f"(d[6]),"+f"(d[7]),"+f"(d[8]),"+f"(d[9]),"+f"(d[10]),"+f"(d[11]),"+f"(d[12]),"+f"(d[13]),"+f"(d[14]),"+f"(d[15])
    :"r"(a0),"r"(a1),"r"(a2),"r"(a3),"l"(db),"r"(sc));
}
__device__ __forceinline__ void wg_rs_48(float* d, uint32_t a0, uint32_t a1, uint32_t a2, uint32_t a3, uint64_t db, uint32_t sc){
  asm volatile("{.reg .pred p; setp.ne.b32 p,%29,0; wgmma.mma_async.sync.aligned.m64n48k16.f32.bf16.bf16 {%0,%1,%2,%3,%4,%5,%6,%7,%8,%9,%10,%11,%12,%13,%14,%15,%16,%17,%18,%19,%20,%21,%22,%23},{%24,%25,%26,%27},%28,p,1,1,1;}"
    :"+f"(d[0]),"+f"(d[1]),"+f"(d[2]),"+f"(d[3]),"+f"(d[4]),"+f"(d[5]),"+f"(d[6]),"+f"(d[7]),"+f"(d[8]),"+f"(d[9]),"+f"(d[10]),"+f"(d[11]),"+f"(d[12]),"+f"(d[13]),"+f"(d[14]),"+f"(d[15]),"+f"(d[16]),"+f"(d[17]),"+f"(d[18]),"+f"(d[19]),"+f"(d[20]),"+f"(d[21]),"+f"(d[22]),"+f"(d[23])
    :"r"(a0),"r"(a1),"r"(a2),"r"(a3),"l"(db),"r"(sc));
}

__device__ __align__(128) const uint32_t g_gt[1024] = {
8388608,41947136,75497984,109056512,142607168,267386880,224920580,267386880,8650832,42209360,75760128,109318656,142869312,267386880,225182732,267386880,
8913056,42471584,76022352,109580880,143131456,267386880,225444884,267386880,9175280,42733808,76284576,109843104,143393552,267386880,225707036,267386880,
9437504,42996032,76546720,110105248,143655696,159646464,225969188,267386880,9699600,43258128,76808864,110367392,143917840,159908612,226231340,267386880,
9961952,43520480,77071088,110629616,144180036,160170760,226493492,267386880,10224048,43782576,77332996,110891524,144442180,160432908,226755644,267386880,
10485764,44044292,77595140,111153668,144704324,160695088,227021828,267386880,10747988,44306516,77857284,111415812,144966468,160957236,227283980,267386880,
11010212,44568740,78119508,111678036,145228612,161219384,227546132,267386880,11272436,44830964,78381732,111940260,145490708,161481532,227808284,267386880,
11534660,45093188,78643876,112202404,145752852,161743648,228070436,267386880,11796756,45355284,78906020,112464548,146014996,162005796,228332588,267386880,
12059108,45617636,79168244,112726772,146277192,162267944,228594740,267386880,12321204,45879732,79430152,112988680,146539336,162530092,228856892,267386880,
12582920,46141448,79692296,113250824,146801480,162796304,229114964,267386880,12845144,46403672,79954440,113512968,147063624,163058452,229377116,267386880,
13107368,46665896,80216664,113775192,147325768,163320600,229639236,267386880,13369592,46928120,80478888,114037416,147587864,163582748,229901388,267386880,
13631816,47190344,80741032,114299560,147850008,163844864,230163572,267386880,13893912,47452440,81003176,114561704,148112152,164107012,230425724,267386880,
14156264,47714792,81265400,114823928,148374348,164369160,230687844,267386880,14418360,47976888,81527308,115085836,148636492,164631308,230949996,267386880,
14680076,48238604,81789452,115347980,148898636,164893488,231216212,267386880,14942300,48500828,82051596,115610124,149160780,165155636,231478364,267386880,
15204524,48763052,82313820,115872348,149422924,165417784,231740484,267386880,15466748,49025276,82576044,116134572,149685020,165679932,232002636,267386880,
15728972,49287500,82838188,116396716,149947164,165942048,232264820,267386880,15991068,49549596,83100332,116658860,150209308,166204196,232526972,267386880,
16253420,49811948,83362556,116921084,267386880,166466344,232789092,267386880,16515516,50074044,83624464,117182992,267386880,166728492,233051244,267386880,
16777232,50335760,83886608,117445136,267386880,166986672,233309348,267386880,17039424,50597952,84148752,117707280,267386880,167248820,233571500,267386880,
17301680,50860208,84410944,117969472,267386880,167510968,233833652,267386880,17563872,51122400,84673200,118231728,267386880,167773116,234095804,267386880,
17826128,51384656,84935344,118493872,267386880,168035232,234357892,267386880,18088192,51646720,85197488,118756016,267386880,168297380,234620044,267386880,
18350576,51909104,85459680,119018208,267386880,168559528,234882196,267386880,18612640,52171168,85721620,119280148,267386880,168821676,235144348,267386880,
18874388,52432916,85983764,119542292,267386880,169083792,235410596,267386880,19136580,52695108,86245908,119804436,267386880,169345940,235672748,267386880,
19398836,52957364,86508100,120066628,267386880,169608088,235934900,267386880,19661028,53219556,86770356,120328884,267386880,169870236,236197052,267386880,
19923284,53481812,87032500,120591028,267386880,170132352,236459140,267386880,20185348,53743876,87294644,120853172,267386880,170394500,236721292,267386880,
20447732,54006260,87556836,121115364,267386880,170656648,236983444,267386880,20709796,54268324,87818776,121377304,267386880,170918796,237245596,267386880,
20971544,54530072,88080920,121639448,267386880,171185072,237503732,267386880,21233736,54792264,88343064,121901592,267386880,171447220,237765884,267386880,
21495992,55054520,88605256,122163784,267386880,171709368,238028004,267386880,21758184,55316712,88867512,122426040,267386880,171971516,238290156,267386880,
22020440,55578968,89129656,122688184,267386880,172233632,238552276,267386880,22282504,55841032,89391800,122950328,267386880,172495780,238814428,267386880,
22544888,56103416,89653992,123212520,267386880,172757928,239076548,267386880,22806952,56365480,89915932,123474460,267386880,173020076,239338700,267386880,
23068700,56627228,90178076,123736604,267386880,173282192,239604980,267386880,23330892,56889420,90440220,123998748,267386880,173544340,239867132,267386880,
23593148,57151676,90702412,124260940,267386880,173806488,240129252,267386880,23855340,57413868,90964668,124523196,267386880,174068636,240391404,267386880,
24117596,57676124,91226812,124785340,267386880,174330752,240653524,267386880,24379660,57938188,91488956,125047484,267386880,174592900,240915676,267386880,
24642044,58200572,91751148,125309676,267386880,174855048,241177796,267386880,24904108,58462636,92013088,125571616,267386880,175117196,241439948,267386880,
25165856,58724384,92275232,125833760,267386880,267386880,249824264,267386880,25428080,58986608,92537376,126095904,267386880,267386880,250086416,267386880,
25690240,59248768,92799600,126358128,267386880,267386880,250348568,267386880,25952464,59510992,93061760,126620288,267386880,192152400,250610720,267386880,
26214752,59773280,93323904,126882432,267386880,192414548,250872872,267386880,26476848,60035376,93586048,127144576,267386880,192676696,251135024,267386880,
26739136,60297664,93848272,127406800,267386880,192938844,251397176,267386880,27001232,60559760,94110244,127668772,267386880,193200992,251663360,267386880,
27263012,60821540,94372388,127930916,267386880,193463140,251925512,267386880,27525236,61083764,94634532,128193060,267386880,193725288,252187664,267386880,
27787396,61345924,94896756,128455284,267386880,193987436,252449816,267386880,28049620,61608148,95158916,128717444,267386880,194249584,252711968,267386880,
28311908,61870436,95421060,128979588,267386880,194511732,252974120,267386880,28574004,62132532,95683204,129241732,267386880,194773880,253236272,267386880,
28836292,62394820,95945428,129503956,267386880,195036028,253498424,267386880,29098388,62656916,96207400,129765928,267386880,195302208,253756496,267386880,
29360168,62918696,96469544,130028072,267386880,195564356,254018648,267386880,29622392,63180920,96731688,130290216,267386880,195826504,254280768,267386880,
29884552,63443080,96993912,130552440,267386880,196088652,254542920,267386880,30146776,63705304,97256072,130814600,267386880,196350800,254805104,267386880,
30409064,63967592,97518216,131076744,267386880,196612948,255067256,267386880,30671160,64229688,97780360,131338888,267386880,196875096,255329376,267386880,
30933448,64491976,98042584,131601112,267386880,197137244,255591528,267386880,31195544,64754072,98304556,131863084,267386880,197399392,255857744,267386880,
31457324,65015852,98566700,132125228,267386880,197661540,256119896,267386880,31719548,65278076,98828844,132387372,267386880,197923688,256382016,267386880,
31981708,65540236,99091068,132649596,267386880,198185836,256644168,267386880,32243932,65802460,99353228,132911756,267386880,198447984,256906352,267386880,
32506220,66064748,99615372,133173900,267386880,198710132,257168504,267386880,32768316,66326844,99877516,133436044,267386880,198972280,257430624,267386880,
33030604,66589132,100139740,133698268,267386880,199234428,257692776,267386880,33292700,66851228,100401712,133960240,267386880,199492576,257950880,267386880,
33554480,67113008,100663856,134222384,267386880,199754724,258213032,267386880,33816672,67375200,100926000,134484528,267386880,200016872,258475184,267386880,
34078864,67637392,101188192,134746720,267386880,200279020,258737336,267386880,34341056,67899584,101450384,135008912,267386880,200541168,258999424,267386880,
34603376,68161904,101712528,135271056,267386880,200803316,259261576,267386880,34865440,68423968,101974672,135533200,267386880,201065464,259523728,267386880,
35127760,68686288,102236864,135795392,267386880,201327612,259785880,267386880,35389824,68948352,102498868,136057396,267386880,201589696,260052128,267386880,
35651636,69210164,102761012,136319540,267386880,201851844,260314280,267386880,35913828,69472356,103023156,136581684,267386880,202113992,260576432,267386880,
36176020,69734548,103285348,136843876,267386880,202376140,260838584,267386880,36438212,69996740,103547540,137106068,267386880,202638288,261100672,267386880,
36700532,70259060,103809684,137368212,267386880,202900436,261362824,267386880,36962596,70521124,104071828,137630356,267386880,203162584,261624976,267386880,
37224916,70783444,104334020,137892548,267386880,203424732,261887128,267386880,37486980,71045508,104596024,138154552,267386880,203690976,262145264,267386880,
37748792,71307320,104858168,138416696,267386880,203953124,262407416,267386880,38010984,71569512,105120312,138678840,267386880,204215272,262669536,267386880,
38273176,71831704,105382504,138941032,267386880,204477420,262931688,267386880,38535368,72093896,105644696,139203224,267386880,204739568,263193808,267386880,
38797688,72356216,105906840,139465368,267386880,205001716,263455960,267386880,39059752,72618280,106168984,139727512,267386880,205263864,263718080,267386880,
39322072,72880600,106431176,139989704,267386880,205526012,263980232,267386880,39584136,73142664,106693180,140251708,267386880,205788096,264246512,267386880,
39845948,73404476,106955324,140513852,267386880,206050244,264508664,267386880,40108140,73666668,107217468,140775996,267386880,206312392,264770784,267386880,
40370332,73928860,107479660,141038188,267386880,206574540,265032936,267386880,40632524,74191052,107741852,141300380,267386880,206836688,265295056,267386880,
40894844,74453372,108003996,141562524,267386880,207098836,265557208,267386880,41156908,74715436,108266140,141824668,267386880,207360984,265819328,267386880,
41419228,74977756,108528332,142086860,267386880,207623132,266081480,267386880,41681292,75239820,108794368,142345024,267386880,207881216,266339648,267386880,};

struct Scratch {
  uint4 H[128 * 28 * 128];
  uint4 sT[2 * 640 * 256];
  uint2 u[640 * 592];
  uint4 stats[2048];
  float cs[2 * 1728];
  unsigned ep[128 * 32], cnt[6 * 32], flagH[128 * 8];
};
__device__ __align__(1024) Scratch g_scr;
#define ST4(c, i) do { } while (0)
#define ST5(r, i) do { } while (0)
#define STAMP(i) do { } while (0)
#define CNT(i) do { } while (0)
#define CNT0() do { } while (0)
#define DUMP() do { } while (0)
#define ST2(i) do { } while (0)
#define ST3(i) do { } while (0)

struct Ptrs {
  const char* x;
  Scratch* S;
  const unsigned short* arr[8];
  const uint32_t* gt;
  const char* w2;
  char* out;
};
struct Params { CUtensorMap mx, mw1a, mw1b, mcs, mw2a, mw2b, mxo; };

constexpr uint32_t OFF_A = 0, OFF_B0 = 49152, OFF_RK = 16384, OFF_HST = 0, OFF_W = 57344, OFF_U = 131072, OFF_F = 154752, OFF_CS = OFF_U;
constexpr uint32_t OFF_KA0 = 114688, OFF_KA1 = 165248, OFF_KB0 = OFF_KA1 + 16384, OFF_KB1 = OFF_KB0 + 12288;
constexpr uint32_t OFF_KT = 207232, OFF_CB = 227712, OFF_ST = 229504, OFF_BAR = 230528, OFF_B2 = 231552, OFF_KV = 232192, SMEM_BYTES = 232448;
constexpr uint32_t OFF_XO = OFF_F, OFF_XC = OFF_F + 21504;
constexpr uint32_t UPS = 1184, USZ = 4736, FSZ = 10496, F5O = 3072, F7O = 6144, F9O = 8320;
constexpr uint32_t T3O = 541, T5O = 666, T7O = 858, T9O = 953;
constexpr uint32_t B_F1 = 0, B_E1 = 160, B_F2 = 320, B_E2 = 544, B_SF = 768, B_XF = 960, B_XR = 784, B_KD = 792, B_CS = 992, B_UB = 808, B_PD = 848, B_MD = 888, B_KG = 928;

__device__ __forceinline__ void mbar_init(uint32_t b, uint32_t c, uint32_t tx) {
  asm volatile("mbarrier.inval.shared::cta.b64 [%0];" ::"r"(b) : "memory");
  asm volatile("st.shared.v2.b32 [%0],{%1,%2};" ::"r"(b), "r"(0x1ffffeu - (tx << 21)), "r"(((0u - c) << 11 & 0x7fffffffu) | ((0u - tx) >> 11 & 0x3ffu)) : "memory");
}
__device__ __forceinline__ void mbar_arrive(uint32_t b) { asm volatile("mbarrier.arrive.shared::cta.b64 _, [%0];" ::"r"(b) : "memory"); }
__device__ __forceinline__ void mbar_arrive_cl(uint32_t rb) { asm volatile("mbarrier.arrive.relaxed.cluster.shared::cluster.b64 _, [%0];" ::"r"(rb) : "memory"); }
__device__ __forceinline__ uint32_t mapa(uint32_t a, uint32_t cta) { uint32_t r; asm volatile("mapa.shared::cluster.u32 %0,%1,%2;" : "=r"(r) : "r"(a), "r"(cta)); return r; }
#define MWAIT(b) asm volatile("{.reg .pred p,q;\nLW%=: add.u32 %0,%0,1; mbarrier.try_wait.parity.shared::cta.b64 p,[%1],0; setp.lt.and.u32 q,%0,2000000,!p; @q bra LW%=;}" : "+r"(bud) : "r"(b) : "memory")
#define MWAIT_CL(b) asm volatile("{.reg .pred p,q;\nLW%=: add.u32 %0,%0,1; mbarrier.try_wait.parity.acquire.cluster.shared::cta.b64 p,[%1],0; setp.lt.and.u32 q,%0,2000000,!p; @q bra LW%=;}" : "+r"(bud) : "r"(b) : "memory")
__device__ __forceinline__ uint32_t mtest(uint32_t b) { uint32_t r; asm volatile("{.reg .pred p; mbarrier.try_wait.parity.shared::cta.b64 p,[%1],0; selp.u32 %0,1,0,p;}" : "=r"(r) : "r"(b) : "memory"); return r; }
__device__ __forceinline__ uint32_t mpeek(uint32_t b) { uint32_t r; asm volatile("{.reg .pred p; mbarrier.test_wait.parity.shared::cta.b64 p,[%1],0; selp.u32 %0,1,0,p;}" : "=r"(r) : "r"(b) : "memory"); return r; }
#define POLL(ptr, tg) asm volatile("{.reg .pred p,q; .reg .u32 v;\nLP%=: add.u32 %0,%0,1; ld.acquire.gpu.global.u32 v,[%1]; setp.ne.u32 p,v,%2; setp.lt.and.u32 q,%0,2000000,p; @q bra LP%=;}" : "+r"(bud) : "l"(ptr), "r"(tg) : "memory")
__device__ __forceinline__ void tma2d(uint32_t dst, const CUtensorMap* tm, uint32_t bar, int c0, int c1) {
  asm volatile("cp.async.bulk.tensor.2d.shared::cluster.global.mbarrier::complete_tx::bytes [%0],[%1,{%3,%4}],[%2];" ::"r"(dst), "l"(tm), "r"(bar), "r"(c0), "r"(c1) : "memory");
}
__device__ __forceinline__ void tma3d(uint32_t dst, const CUtensorMap* tm, uint32_t bar, int c0, int c1, int c2) {
  asm volatile("cp.async.bulk.tensor.3d.shared::cluster.global.mbarrier::complete_tx::bytes [%0],[%1,{%3,%4,%5}],[%2];" ::"r"(dst), "l"(tm), "r"(bar), "r"(c0), "r"(c1), "r"(c2) : "memory");
}
template <int OPT>
__device__ __forceinline__ void wait_tma(uint32_t& bud, uint32_t wb, uint32_t d, const CUtensorMap* ma, uint32_t bar, int c0, int k, uint32_t d2, const CUtensorMap* mb, int c2) {
#define WTMA(S) asm volatile("{.reg .pred p,q;" S "\nLW%=: add.u32 %0,%0,1; mbarrier.try_wait.parity.shared::cta.b64 p,[%1],0; setp.lt.and.u32 q,%0,2000000,!p; @q bra LW%=;\nLX%=:\n" \
               "cp.async.bulk.tensor.3d.shared::cluster.global.mbarrier::complete_tx::bytes [%2],[%3,{%5,%6,0}],[%4];\n" \
               "cp.async.bulk.tensor.2d.shared::cluster.global.mbarrier::complete_tx::bytes [%7],[%8,{%9,%6}],[%4];}" \
               : "+r"(bud) : "r"(wb), "r"(d), "l"(ma), "r"(bar), "r"(c0), "r"(k), "r"(d2), "l"(mb), "r"(c2) : "memory")
  if (OPT) WTMA("setp.eq.u32 p,%1,0; @p bra LX%=;"); else WTMA("");
}
__device__ __forceinline__ void bulk_ld(uint32_t dst, const void* src, uint32_t bytes, uint32_t bar) {
  asm volatile("cp.async.bulk.shared::cluster.global.mbarrier::complete_tx::bytes [%0],[%1],%2,[%3];" ::"r"(dst), "l"(src), "r"(bytes), "r"(bar) : "memory");
}
__device__ __forceinline__ void wait_ld(uint32_t& bud, uint32_t wb, uint32_t dst, const void* src, uint32_t bar) {
  asm volatile("{.reg .pred p,q;\nLW%=: add.u32 %0,%0,1; mbarrier.try_wait.parity.shared::cta.b64 p,[%1],0; setp.lt.and.u32 q,%0,2000000,!p; @q bra LW%=;\n"
               "cp.async.bulk.shared::cluster.global.mbarrier::complete_tx::bytes [%2],[%3],8192,[%4];}" : "+r"(bud) : "r"(wb), "r"(dst), "l"(src), "r"(bar) : "memory");
}
__device__ __forceinline__ void bulk_st(void* dst, uint32_t src, uint32_t bytes) {
  asm volatile("cp.async.bulk.global.shared::cta.bulk_group [%0],[%1],%2;\n cp.async.bulk.commit_group;" ::"l"(dst), "r"(src), "r"(bytes) : "memory");
}
__device__ __forceinline__ uint32_t elect() { uint32_t el; asm volatile("{.reg .pred p; elect.sync _|p,0xffffffff; selp.u32 %0,1,0,p;}" : "=r"(el)); return el; }
#define BAR_SYNC(id, n) asm volatile("bar.sync %0,%1;" ::"n"(id), "n"(n) : "memory")
#define BAR_SYNCR(id, n) asm volatile("bar.sync %0,%1;" ::"r"(id), "n"(n) : "memory")
#define BAR_ARRIVE(id, n) asm volatile("bar.arrive %0,%1;" ::"n"(id), "n"(n) : "memory")
#define FENCE_ASYNC_G() asm volatile("fence.proxy.async.global;" ::: "memory")
#define PIN(a, n) _Pragma("unroll") for (int j_ = 0; j_ < n; j_++) asm volatile("" : "+f"(a[j_])::"memory")
#define FENCE_ASYNC_SH() asm volatile("fence.proxy.async.shared::cta;" ::: "memory")
#define WG_FENCE() asm volatile("wgmma.fence.sync.aligned;" ::: "memory")
#define WG_COMMIT() asm volatile("wgmma.commit_group.sync.aligned;" ::: "memory")
#define WG_WAIT(n) asm volatile("wgmma.wait_group.sync.aligned %0;" ::"n"(n) : "memory")
__device__ __forceinline__ uint64_t mkdesc(uint32_t addr, uint32_t lbo, uint32_t sbo, uint32_t type) {
  uint32_t lo = ((addr & 0x3FFFF) >> 4) | (lbo << 16), hi = sbo | (type << 30);
  return ((uint64_t)hi << 32) | lo;
}
__device__ __forceinline__ uint64_t dadd(uint64_t d, int o) { return (d & 0xffffffff00000000ull) | (uint32_t)((uint32_t)d + o); }
__device__ __forceinline__ uint32_t pack(float lo, float hi) { uint32_t r; asm("cvt.rn.bf16x2.f32 %0,%1,%2;" : "=r"(r) : "f"(hi), "f"(lo)); return r; }
__device__ __forceinline__ float blo(uint32_t v) { return __uint_as_float(v << 16); }
__device__ __forceinline__ float bhi(uint32_t v) { return __uint_as_float(v & 0xffff0000u); }
__device__ __forceinline__ float tanh_ap(float x) { float r; asm("tanh.approx.f32 %0,%1;" : "=f"(r) : "f"(x)); return r; }
__device__ __forceinline__ float ex2(float x) { float r; asm("ex2.approx.ftz.f32 %0,%1;" : "=f"(r) : "f"(x)); return r; }
__device__ __forceinline__ float rsq(float x) { float r; asm("rsqrt.approx.ftz.f32 %0,%1;" : "=f"(r) : "f"(x)); return r; }
__device__ __forceinline__ uint32_t hfma2(uint32_t a, uint32_t b, uint32_t c) { uint32_t r; asm("fma.rn.bf16x2 %0,%1,%2,%3;" : "=r"(r) : "r"(a), "r"(b), "r"(c)); return r; }
__device__ __forceinline__ uint32_t hmul2(uint32_t a, uint32_t b) { uint32_t r; asm("mul.rn.bf16x2 %0,%1,%2;" : "=r"(r) : "r"(a), "r"(b)); return r; }
__device__ __forceinline__ uint32_t hadd2(uint32_t a, uint32_t b) { uint32_t r; asm("add.rn.bf16x2 %0,%1,%2;" : "=r"(r) : "r"(a), "r"(b)); return r; }
__device__ __forceinline__ uint32_t htanh2(uint32_t a) { uint32_t r; asm("tanh.approx.bf16x2 %0,%1;" : "=r"(r) : "r"(a)); return r; }
__device__ __forceinline__ uint32_t lds32(uint32_t a) { uint32_t v; asm volatile("ld.shared.b32 %0,[%1];" : "=r"(v) : "r"(a) : "memory"); return v; }
__device__ __forceinline__ float ldsb(uint32_t a) { uint32_t v; asm volatile("ld.shared.u16 %0,[%1];" : "=r"(v) : "r"(a) : "memory"); return blo(v); }
__device__ __forceinline__ float ldsf(uint32_t a) { float v; asm volatile("ld.shared.f32 %0,[%1];" : "=f"(v) : "r"(a) : "memory"); return v; }
__device__ __forceinline__ float2 lds64f(uint32_t a) { float2 v; asm volatile("ld.shared.v2.f32 {%0,%1},[%2];" : "=f"(v.x), "=f"(v.y) : "r"(a) : "memory"); return v; }
__device__ __forceinline__ float4 lds128f(uint32_t a) { float4 v; asm volatile("ld.shared.v4.f32 {%0,%1,%2,%3},[%4];" : "=f"(v.x), "=f"(v.y), "=f"(v.z), "=f"(v.w) : "r"(a) : "memory"); return v; }
__device__ __forceinline__ uint4 lds128(uint32_t a) { uint4 v; asm volatile("ld.shared.v4.b32 {%0,%1,%2,%3},[%4];" : "=r"(v.x), "=r"(v.y), "=r"(v.z), "=r"(v.w) : "r"(a) : "memory"); return v; }
__device__ __forceinline__ void sts32(uint32_t a, uint32_t v) { asm volatile("st.shared.b32 [%0],%1;" ::"r"(a), "r"(v) : "memory"); }
__device__ __forceinline__ void stsf(uint32_t a, float v) { asm volatile("st.shared.f32 [%0],%1;" ::"r"(a), "f"(v) : "memory"); }
__device__ __forceinline__ void sts64f(uint32_t a, float x, float y) { asm volatile("st.shared.v2.f32 [%0],{%1,%2};" ::"r"(a), "f"(x), "f"(y) : "memory"); }
__device__ __forceinline__ void sts16(uint32_t a, uint32_t v) { asm volatile("st.shared.u16 [%0],%1;" ::"r"(a), "r"(v) : "memory"); }
__device__ __forceinline__ void sts128(uint32_t a, uint32_t x, uint32_t y, uint32_t z, uint32_t w) { asm volatile("st.shared.v4.b32 [%0],{%1,%2,%3,%4};" ::"r"(a), "r"(x), "r"(y), "r"(z), "r"(w) : "memory"); }
__device__ __forceinline__ void sts128f(uint32_t a, float x, float y, float z, float w) { asm volatile("st.shared.v4.f32 [%0],{%1,%2,%3,%4};" ::"r"(a), "f"(x), "f"(y), "f"(z), "f"(w) : "memory"); }
__device__ __forceinline__ void ldsm4(uint32_t* r, uint32_t a) { asm volatile("ldmatrix.sync.aligned.m8n8.x4.shared.b16 {%0,%1,%2,%3},[%4];" : "=r"(r[0]), "=r"(r[1]), "=r"(r[2]), "=r"(r[3]) : "r"(a) : "memory"); }
__device__ __forceinline__ void ldsm4t(uint32_t* r, uint32_t a) { asm volatile("ldmatrix.sync.aligned.m8n8.x4.trans.shared.b16 {%0,%1,%2,%3},[%4];" : "=r"(r[0]), "=r"(r[1]), "=r"(r[2]), "=r"(r[3]) : "r"(a) : "memory"); }
__device__ __forceinline__ void stsm4(uint32_t a, uint32_t r0, uint32_t r1, uint32_t r2, uint32_t r3) { asm volatile("stmatrix.sync.aligned.m8n8.x4.shared.b16 [%0],{%1,%2,%3,%4};" ::"r"(a), "r"(r0), "r"(r1), "r"(r2), "r"(r3) : "memory"); }
__device__ __forceinline__ void stsm4t(uint32_t a, uint32_t r0, uint32_t r1, uint32_t r2, uint32_t r3) { asm volatile("stmatrix.sync.aligned.m8n8.x4.trans.shared.b16 [%0],{%1,%2,%3,%4};" ::"r"(a), "r"(r0), "r"(r1), "r"(r2), "r"(r3) : "memory"); }
__device__ __forceinline__ void mma16(float* c, const uint32_t* a, uint32_t b0, uint32_t b1) {
  asm volatile("mma.sync.aligned.m16n8k16.row.col.f32.bf16.bf16.f32 {%0,%1,%2,%3},{%4,%5,%6,%7},{%8,%9},{%0,%1,%2,%3};" : "+f"(c[0]), "+f"(c[1]), "+f"(c[2]), "+f"(c[3]) : "r"(a[0]), "r"(a[1]), "r"(a[2]), "r"(a[3]), "r"(b0), "r"(b1));
}
__device__ __forceinline__ void mma8(float* c, uint32_t a0, uint32_t a1, uint32_t b0) {
  asm volatile("mma.sync.aligned.m16n8k8.row.col.f32.bf16.bf16.f32 {%0,%1,%2,%3},{%4,%5},{%6},{%0,%1,%2,%3};" : "+f"(c[0]), "+f"(c[1]), "+f"(c[2]), "+f"(c[3]) : "r"(a0), "r"(a1), "r"(b0));
}
__device__ __forceinline__ uint32_t ldg16(const void* p) { uint32_t v; asm volatile("ld.global.nc.u16 %0,[%1];" : "=r"(v) : "l"(p)); return v; }
__device__ __forceinline__ uint32_t ldg32(const void* p) { uint32_t v; asm volatile("ld.global.nc.b32 %0,[%1];" : "=r"(v) : "l"(p)); return v; }
__device__ __forceinline__ uint2 lds64(uint32_t a) { uint2 v; asm volatile("ld.shared.v2.b32 {%0,%1},[%2];" : "=r"(v.x), "=r"(v.y) : "r"(a) : "memory"); return v; }
__device__ __forceinline__ uint4 ldg128(const void* p) { uint4 v; asm volatile("ld.global.nc.v4.b32 {%0,%1,%2,%3},[%4];" : "=r"(v.x), "=r"(v.y), "=r"(v.z), "=r"(v.w) : "l"(p)); return v; }
__device__ __forceinline__ float bfround(float x) { return bhi(pack(0.f, x)); }
__device__ __forceinline__ void cis(float er, float ang, float& re, float& im) {
  float mg = ex2(er), s, c;
  asm("sin.approx.ftz.f32 %0,%1;" : "=f"(s) : "f"(ang));
  asm("cos.approx.ftz.f32 %0,%1;" : "=f"(c) : "f"(ang));
  re = mg * c; im = mg * s;
}
__device__ __forceinline__ float redang(float f) { return (f - ((f + 12582912.f) - 12582912.f)) * 6.283185307179586f; }
#define CSQ(orr, oi, ar, ai) do { float _r = (ar) * (ar) - (ai) * (ai); float _i = ((ar) + (ar)) * (ai); orr = _r; oi = _i; } while (0)
#define CMUL(orr, oi, ar, ai, br, bi) do { float _r = (ar) * (br) - (ai) * (bi); float _i = (ar) * (bi) + (ai) * (br); orr = _r; oi = _i; } while (0)

__device__ __forceinline__ uint32_t movm(uint32_t a) { uint32_t r; asm volatile("movmatrix.sync.aligned.m8n8.trans.b16 %0,%1;" : "=r"(r) : "r"(a)); return r; }
__device__ __forceinline__ uint4 ldrel128(const void* p) { uint4 v; asm volatile("ld.relaxed.gpu.global.v4.u32 {%0,%1,%2,%3},[%4];" : "=r"(v.x), "=r"(v.y), "=r"(v.z), "=r"(v.w) : "l"(p) : "memory"); return v; }
__device__ __forceinline__ uint2 ldg64(const void* p) { uint2 v; asm volatile("ld.global.nc.v2.b32 {%0,%1},[%2];" : "=r"(v.x), "=r"(v.y) : "l"(p)); return v; }

__device__ __forceinline__ int tA(int n) { return (n >> 1) * 448 + (n & 1) * 192; }
__device__ __forceinline__ int tH(int n) { return min(max(tA(n) - 32 + (n & 1) * 224, 0), 1664); }
__device__ __forceinline__ int tord(int n, int p) { return p < 2 ? n ^ p : ((n & 6) ^ 2) + (p & 1); }
__device__ __forceinline__ int skipq(int nt, int kh) { return 7 * (kh ? (nt < 2 ? 3 : nt ^ 3) : min(nt, 2)) + 6; }
__device__ __forceinline__ int lntok(int tb, int g) { return (tb >> 2) * 64 + (tb & 3) * 8 + (g & 1) + (g & 2) * 2 + (g & 4) * 8; }

__device__ __forceinline__ void consumer(const Ptrs& Q, const uint32_t* pre, uint32_t sb, int m, int nt, int kh, int wid, int lane, long long tstart) {
  const uint32_t bb = sb + OFF_BAR;
  const int wg = wid >> 2;
  const int g = lane >> 2, t = lane & 3;
  uint32_t bud = 16;
  {
    const int tb = blockIdx.x, tok = pre[20];
    const uint32_t *xa = pre, *xb = pre + 10;
    ST4(threadIdx.x == 0, 0);
    {
      const int q = 8 + wid * 15 + lane;
      uint32_t tx = q < 20 ? q & 1 ? 14336 : 30720 : 0, c = 8;
      if (q >= 40) tx = q < 47 ? 10240 : 18432;
      if (q >= 68) tx = q == 96 ? 21504 : q >= 120 ? 5120 : q == 101 ? USZ + 2048 : (unsigned)(q - 102) < 4u ? USZ : 0;
      if (tx) c = 0;
      else if (q >= 96) c = q == 98 ? 1 : (unsigned)(q - 106) < 5u ? 2 : 4;
      if (lane < 15 && q >> 2 != 5 && q < 124) mbar_init(bb + q * 8, c, tx);
#pragma unroll
      for (int i = 0; i < 5; i++) sts128(sb + OFF_KT + threadIdx.x * 16 + i * 4096, 0, 0, 0, 0);
      BAR_ARRIVE(1, 512);
    }
    asm volatile("setmaxnreg.inc.sync.aligned.u32 152;");
    ST4(threadIdx.x == 0, 3);
    CNT0();
    float cs[4] = {0.f, 0.f, 0.f, 0.f}, ca[4] = {0.f, 0.f, 0.f, 0.f}, cb[4] = {0.f, 0.f, 0.f, 0.f};
#pragma unroll
    for (int j = 0; j < 10; j += 2) {
      const uint32_t a[4] = {xa[j], xb[j], xa[j + 1], xb[j + 1]};
      mma16(cs, a, 0x3f803f80, 0x3f803f80); mma16(ca, a, a[0], a[2]); mma16(cb, a, a[1], a[3]);
    }
    if (threadIdx.x == 0) STAMP(9);
    if (t == g >> 1) sts128f(sb + OFF_ST + wid * 128 + g * 16, cs[0], g & 1 ? ca[1] : ca[0], cs[2], g & 1 ? cb[3] : cb[2]);
    BAR_SYNC(0, 288);
    asm volatile("barrier.cluster.arrive.relaxed.aligned;" ::: "memory");
    float4 v[8];
#pragma unroll
    for (int j = 0; j < 8; j++) v[j] = lds128f(sb + OFF_ST + j * 128 + g * 16);
#pragma unroll
    for (int o = 4; o; o >>= 1)
#pragma unroll
      for (int j = 0; j < o; j++) { v[j].x += v[j + o].x; v[j].y += v[j + o].y; v[j].z += v[j + o].z; v[j].w += v[j + o].w; }
    uint32_t rh[2], rl[2], nb[2];
#pragma unroll
    for (int u = 0; u < 2; u++) {
      const float s = (u ? v[0].z : v[0].x) * (-1.f / 640.f);
      const float var = fmaxf(fmaf(u ? v[0].w : v[0].y, 1.f / 640.f, -s * s), 0.f);
      const float r1 = rsq(var + 1e-5f);
      rh[u] = pack(r1, r1); rl[u] = pack(r1 - blo(rh[u]), r1 - blo(rh[u])); nb[u] = pack(s * r1, s * r1);
      if (wid == 0 && t == u) {
        const float q2 = fmaf(var * r1, r1, 1e-5f), r2 = rsq(q2), sg = (var + 1e-5f) * r1 * q2 * r2;
        const uint32_t mh = pack(s, s), ms = pack(s - blo(mh), sg);
        Q.S->stats[tok + 2 * u] = make_uint4(mh, ms, pack(sg - bhi(ms), 0.f), __float_as_uint(0.7978845608028654f * r1 * r2) & ~128u);
      }
    }
    if (threadIdx.x == 0) STAMP(10);
    uint2* dst = Q.S->u + (wid * 80 + (g & 1)) * 592 + (tb & 3) * 148 + 16 + (tb >> 2) * 4 + t;
#pragma unroll
    for (int j = 0; j < 10; j++)
      dst[(j < 8 ? (g >> 1) * 8 + (j >> 2) * 32 + (j & 3) * 2 : (g >> 1) * 4 + 64 + (j & 1) * 2) * 592] =
          make_uint2(movm(hfma2(xa[j], rh[0], hfma2(xa[j], rl[0], nb[0]))), movm(hfma2(xb[j], rh[1], hfma2(xb[j], rl[1], nb[1]))));
    if (threadIdx.x == 0) STAMP(26);
    BAR_ARRIVE(2, 320);
  }
  float sc;
  {
    float acc[112];
    {
      const uint64_t db0 = mkdesc(sb + OFF_B0, 256, 64, 1);
      uint32_t la = sb + OFF_A + (wid * 16 + (lane & 15)) * 128 + (((lane >> 4) ^ (lane & 7)) << 4);
      int sa = 0, s = 0;
      uint32_t ok = 0, X[4], Y[4], Z[4];
      MWAIT(bb + B_F1);
      if (threadIdx.x == 0) STAMP(1);
      ldsm4(X, la);
      uint64_t db = db0, dh = dadd(db0, 512);
#define G1STAGE(X, Y, Z, LAST) \
        WG_FENCE(); \
        wg_rs_128(acc, X[0], X[1], X[2], X[3], db, p); \
        ldsm4(Y, (la ^ 32) + sa); \
        wg_rs_96(acc + 64, X[0], X[1], X[2], X[3], dh, p); \
        WG_COMMIT(); \
        if (LAST == 2 && p == 20) break; \
        WG_WAIT(1); \
        if (ok && elect()) mbar_arrive(bb + B_E1 - 8 + 8 * p); \
        ok = mpeek(bb + B_F1 + 8 + 8 * p);        \
        if (p & 1) sa = sa == 32768 ? 0 : sa + 16384; \
        la ^= 64; \
        if (LAST == 1 && p == 19) {        \
          BAR_SYNC(7, 288); \
          la = lane < 16 ? sb + OFF_CB + (wid * 16 + lane) * 16 : sb + OFF_RK + 112; \
          sa = 0; \
        } \
        WG_FENCE(); \
        wg_rs_128(acc, Y[0], Y[1], Y[2], Y[3], dadd(db, 128), 1); \
        ldsm4(Z, la + sa); \
        wg_rs_96(acc + 64, Y[0], Y[1], Y[2], Y[3], dadd(dh, 128), 1); \
        WG_COMMIT(); \
        ST2(p * 3); ST2(p * 3 + 1); \
        if (!ok) {         \
          WG_WAIT(0); \
          if (elect()) mbar_arrive(bb + B_E1 + 8 * p); \
          MWAIT(bb + B_F1 + 8 + 8 * p); \
          ldsm4(Z, la + sa); \
          CNT(23); \
        } \
        ST2(p * 3 + 2); \
        s = (s + 1024) & 3072; \
        db = dadd(db0, s); dh = dadd(db, 512); \
        if (LAST == 1 && p == 19) { db = mkdesc(sb + OFF_RK, 1, 9, 0); dh = dadd(db, 144); } \
        WG_WAIT(1); \
        p++;
#pragma unroll 1
      for (int p = 0;;) {
        G1STAGE(X, Y, Z, 0)
        G1STAGE(Z, X, Y, 1)
        G1STAGE(Y, Z, X, 2)
      }
    }
    const float s0 = ldsf(sb + OFF_CB + (wid * 16 + g) * 16 + 12), s1 = ldsf(sb + OFF_CB + (wid * 16 + g) * 16 + 140);
    WG_WAIT(0);
    PIN(acc, 112);
    if (elect()) mbar_arrive(bb + B_E1 + 8 * 19);
    asm volatile("setmaxnreg.dec.sync.aligned.u32 144;");
    if (threadIdx.x == 0) STAMP(2);
    uint32_t hst = sb + OFF_HST + (lane >> 4) * 2048 + (wid * 16 + ((lane & 15) ^ (kh * 8))) * 16;
    const float k0 = 0.07023815775f * s0 * s0 * s0, k1 = 0.07023815775f * s1 * s1 * s1;
    sc = 0.31332853432887503f * (kh ? s1 : s0);
#define GELU(v, s, k) fmaf(v, tanh_ap(fmaf(v * v, k, s) * v), v)
    asm volatile("barrier.cluster.wait.aligned;" ::: "memory");
    MWAIT(bb + B_E1 + 8 * 19);
#pragma unroll 1
    for (int h = 0; h < 2; h++) {
#pragma unroll
      for (int i = 0; i < 14; i += 2) {
        uint32_t r[4];
#pragma unroll
        for (int u = 0; u < 2; u++) {
          const float* a = acc + 4 * (i + u);
          r[2 * u] = pack(GELU(a[0], s0, k0), GELU(a[1], s0, k0));
          r[2 * u + 1] = pack(GELU(a[2], s1, k1), GELU(a[3], s1, k1));
        }
        stsm4(hst + i * 2048, r[0], r[1], r[2], r[3]);
      }
#pragma unroll
      for (int j = 0; j < 56; j++) acc[j] = acc[j + 56];
      hst += 14 * 2048;
      FENCE_ASYNC_SH();
      asm volatile("bar.arrive %0,288;" ::"r"(4 + h) : "memory");
    }
  }
  float acc[80];
  if (threadIdx.x == 0) STAMP(4);
  {
    const int skip = skipq(nt, kh);
    const uint64_t da0 = mkdesc(sb + wg * 1024, 128, 8, 0), db0 = mkdesc(sb + OFF_W, 256, 64, 1);
    int ao = 0, wo = 0, ip = 0;
    uint32_t ok = 0;
    MWAIT(bb + B_F2);
#pragma unroll 1
    for (int i = 0; i < 28;) {
      const uint64_t da = dadd(da0, ao), db = dadd(db0, wo);
      ST2(64 + i * 3);
      WG_FENCE();
      wg_ss_160(acc, da, db, i);
      WG_COMMIT();
      WG_WAIT(1);
      if (ok && elect()) mbar_arrive(bb + B_E2 + 8 * ip);
      WG_FENCE();
      wg_ss_160(acc, dadd(da, 256), dadd(db, 128), 1);
      WG_COMMIT();
      const int in = i + 1 + (i + 1 == skip);
      ok = mpeek(bb + B_F2 + 8 * in);
      ST2(64 + i * 3 + 1);
      if (!ok) {
        WG_WAIT(0);
        if (elect()) mbar_arrive(bb + B_E2 + 8 * i);
        MWAIT(bb + B_F2 + 8 * in);
        CNT(24);
      }
      ST2(64 + i * 3 + 2);
      ao += 512 * (in - i); if (ao == 3584) ao = 0;
      wo += 768 * (in - i); if (wo >= 6 * 768) wo -= 6 * 768;
      ip = i; i = in;
    }
  }

  asm volatile("mov.u32 %0,%%tid.x;" : "=r"(lane));
  wid = lane >> 5; lane &= 31;
  const int row = (wid * 4 + (lane >> 3)) * 5;
  const uint4* sp = Q.S->sT + (lds32(sb + OFF_ST + 512) + nt * 160 + row) * 256 + m * 16 + kh * 8 + (lane & 7);
  uint4 sv[5];
#pragma unroll
  for (int j = 0; j < 4; j++) sv[j] = ldrel128(sp + j * 256);
  WG_WAIT(0);
  PIN(acc, 80);
  if (threadIdx.x == 0) STAMP(6);
  const uint32_t xc = sb + OFF_XC + wid * 2560 + lane * 16, xf = bb + B_XF + (wid >> 1) * 8;
  MWAIT(bb + B_XR);
  {
    const uint32_t rx = mapa(xc, kh ^ 1), rb = mapa(xf, kh ^ 1);
#pragma unroll
    for (int i = 0; i < 5; i++)
      asm volatile("st.async.shared::cluster.mbarrier::complete_tx::bytes.v4.b32 [%0],{%1,%2,%3,%4},[%5];" ::"r"(rx + i * 512), "r"(pack(acc[16 * i + 2], acc[16 * i + 3])), "r"(pack(acc[16 * i + 6], acc[16 * i + 7])),
                   "r"(pack(acc[16 * i + 10], acc[16 * i + 11])), "r"(pack(acc[16 * i + 14], acc[16 * i + 15])), "r"(rb) : "memory");
  }
  if (threadIdx.x == 0) STAMP(23);
#define SSTAGE(j) { \
    while (min(min(sv[j].x, sv[j].y), min(sv[j].z, sv[j].w)) == 0 && ++bud < 2000000) sv[j] = ldrel128(sp + j * 256); \
    const int r = row + j; \
    sts128(sb + (r < 128 ? OFF_KT : OFF_U - 16384) + r * 128 + (((lane ^ r) & 7) << 4), ~sv[j].x, ~sv[j].y, ~sv[j].z, ~sv[j].w); }
  MWAIT(bb + B_SF);
  SSTAGE(0) SSTAGE(1) SSTAGE(2) SSTAGE(3)
  sv[4] = ldrel128(sp + 1024);
  MWAIT(xf);
  if (threadIdx.x == 0) STAMP(24);
  uint32_t gt[20];
#pragma unroll
  for (int j = 0; j < 5; j++) {
    const int jj = j == 4 ? (nt & 1 ? 0 : 4) : j + (nt & 1);
    const uint4 p4 = lds128(xc + j * 512);
    const uint32_t pv[4] = {p4.x, p4.y, p4.z, p4.w};
#pragma unroll
    for (int u = 0; u < 4; u++) {
      const int i = 4 * j + u;
      const float2 cv = lds64f(sb + OFF_B2 + (lane & 3) * 8 + jj * 128 + u * 32);
      const float z0 = fmaf(acc[4 * i] + blo(pv[u]), sc, cv.x), z1 = fmaf(acc[4 * i + 1] + bhi(pv[u]), sc, cv.y);
      gt[i] = pack(fmaf(z0, tanh_ap(z0), z0), fmaf(z1, tanh_ap(z1), z1));
    }
  }
  const uint32_t sa = sb + OFF_KT + lane * 128 + ((wid ^ (m & 1) ^ (lane & 7)) << 4);
  const uint32_t xa = sb + OFF_XO + (wid * 8 + (lane & 7)) * 336 + (lane >> 3) * 16;
#pragma unroll
  for (int i = 0; i < 20; i++) asm volatile("" : "+r"(gt[i])::"memory");
  if (threadIdx.x == 0) STAMP(15);
  uint32_t sr[20], xr[20];
#pragma unroll
  for (int j = 0; j < 5; j++) ldsm4(xr + 4 * j, xa + (j == 4 ? (nt & 1 ? 0 : 4) : j + (nt & 1)) * 64);
  SSTAGE(4)
  if (threadIdx.x == 0) STAMP(25);
  BAR_SYNC(8, 256);
  if (threadIdx.x == 0) STAMP(16);
#pragma unroll
  for (int j = 0; j < 5; j++) {
    const int jj = j == 4 ? (nt & 1 ? 0 : 4) : j + (nt & 1);
    ldsm4t(sr + 4 * j, sa + (jj == 4 ? OFF_U - OFF_KT : jj * 4096));
  }
#pragma unroll
  for (int j = 0; j < 5; j++) {
    const int jj = j == 4 ? (nt & 1 ? 0 : 4) : j + (nt & 1), i = 4 * j;
    stsm4(xa + jj * 64, hfma2(sr[i], gt[i], xr[i]), hfma2(sr[i + 1], gt[i + 1], xr[i + 1]), hfma2(sr[i + 2], gt[i + 2], xr[i + 2]), hfma2(sr[i + 3], gt[i + 3], xr[i + 3]));
  }
  __syncwarp();
#pragma unroll
  for (int j = 0; j < 5; j++) {
    const int r = j < 4 ? (lane >> 3) + (j & 1) * 4 : lane >> 2, c = j < 4 ? (lane & 7) * 16 + (j >> 1) * 128 : (lane & 3) * 16 + 256;
    *(uint4*)(Q.out + (m * 128 + wid * 16 + kh * 8 + r) * 1280 + nt * 320 + c) = lds128(sb + OFF_XO + (wid * 8 + r) * 336 + c);
  }
  if (threadIdx.x == 0) STAMP(7);
  DUMP();
}

#define ST8(a, V, o) sts128(a, pack(V[o], V[o + 1]), pack(V[o + 2], V[o + 3]), pack(V[o + 4], V[o + 5]), pack(V[o + 6], V[o + 7]))
struct KG { float wr[8], wi[8], er[8], ei[8], yr, yi, sr, si; };
__device__ __forceinline__ void kgen_p(KG& k, uint32_t p0, uint32_t p1, uint32_t p2) {
  const float dt = bfround(ex2(blo(p2) * 1.4426950408889634f));
  const float ar = -bfround(ex2(blo(p0) * 1.4426950408889634f)) * dt * 1.4426950408889634f;
  const float ai = bhi(p0) * dt * 0.15915494309189535f;
  float *wr = k.wr, *wi = k.wi, *er = k.er, *ei = k.ei, z1r, z1i, z2r, z2i, z4r, z4i;
  wr[0] = 2.f * dt * blo(p1); wi[0] = -2.f * dt * bhi(p1);
  cis(ar, -redang(ai), z1r, z1i);
  cis(ar * 64.f, redang(ai * 64.f), k.sr, k.si);
  CSQ(z2r, z2i, z1r, z1i); CSQ(z4r, z4i, z2r, z2i);
  CSQ(er[1], ei[1], z4r, -z4i); CSQ(er[2], ei[2], er[1], ei[1]); CSQ(er[4], ei[4], er[2], ei[2]);
  CSQ(k.yr, k.yi, k.sr, -k.si); CSQ(k.yr, k.yi, k.yr, k.yi);
  CMUL(wr[1], wi[1], wr[0], wi[0], z1r, z1i);
  CMUL(wr[2], wi[2], wr[0], wi[0], z2r, z2i); CMUL(wr[3], wi[3], wr[1], wi[1], z2r, z2i);
#pragma unroll
  for (int i = 0; i < 4; i++) CMUL(wr[4 + i], wi[4 + i], wr[i], wi[i], z4r, z4i);
  CMUL(er[3], ei[3], er[1], ei[1], er[2], ei[2]);
#pragma unroll
  for (int i = 1; i < 4; i++) CMUL(er[4 + i], ei[4 + i], er[i], ei[i], er[4], ei[4]);
}
__device__ __forceinline__ void kgen_w(KG& k, uint32_t wb) {
  float *wr = k.wr, *wi = k.wi, yr = k.yr, yi = k.yi;
  ST8(wb, wr, 0); ST8(wb + 1024, wi, 0);
#pragma unroll
  for (int i = 0; i < 4; i++) CMUL(wr[i], wi[i], wr[2 * i], wi[2 * i], yr, yi);
  CMUL(wr[4], wi[4], wr[0], wi[0], yr, yi); CMUL(wr[5], wi[5], wr[2], wi[2], yr, yi);
  CSQ(yr, yi, yr, yi);
  CMUL(wr[6], wi[6], wr[0], wi[0], yr, yi); CMUL(wr[7], wi[7], wr[2], wi[2], yr, yi);
  ST8(wb + 2048, wr, 0); ST8(wb + 3072, wi, 0);
  CMUL(wr[0], wi[0], wr[4], wi[4], yr, yi); CMUL(wr[1], wi[1], wr[6], wi[6], yr, yi);
  CMUL(wr[2], wi[2], wr[0], wi[0], yr, yi); CMUL(wr[3], wi[3], wr[1], wi[1], yr, yi);
  CMUL(wr[4], wi[4], wr[2], wi[2], yr, yi);
  sts128(wb + 4096, pack(wr[0], wr[1]), pack(wr[2], wr[3]), pack(wr[4], 0.f), 0);
  sts128(wb + 5120, pack(wi[0], wi[1]), pack(wi[2], wi[3]), pack(wi[4], 0.f), 0);
}
__device__ __forceinline__ void kgen_e(KG& k, uint32_t ab) {
  float *er = k.er, *ei = k.ei;
  er[0] = 1.f; ei[0] = 0.f;
  ST8(ab, er, 0); ST8(ab + 1024, ei, 0);
  er[0] = k.sr; ei[0] = k.si;
#pragma unroll
  for (int i = 1; i < 8; i++) CMUL(er[i], ei[i], er[i], ei[i], k.sr, k.si);
  ST8(ab + 2048, er, 0); ST8(ab + 3072, ei, 0);
#pragma unroll
  for (int u = 2; u < 4; u++) {
#pragma unroll
    for (int i = 0; i < 8; i++) CMUL(er[i], ei[i], er[i], ei[i], k.sr, k.si);
    ST8(ab + u * 2048, er, 0); ST8(ab + u * 2048 + 1024, ei, 0);
  }
}
__device__ __forceinline__ uint32_t uadr(int c) { return 128 + (c & 3) * UPS + (c >> 2) * 16; }
__device__ __forceinline__ void add8(float* s, uint4 v) {
  s[0] += blo(v.x); s[1] += bhi(v.x); s[2] += blo(v.y); s[3] += bhi(v.y); s[4] += blo(v.z); s[5] += bhi(v.z); s[6] += blo(v.w); s[7] += bhi(v.w);
}

__device__ __forceinline__ uint4 add4(uint4 a, uint4 b) { return make_uint4(hadd2(a.x, b.x), hadd2(a.y, b.y), hadd2(a.z, b.z), hadd2(a.w, b.w)); }

__device__ __forceinline__ void prep(uint32_t u, uint32_t f, int c) {
  uint32_t a0 = u + uadr(c), a1 = u + uadr(c - 1), a2 = u + uadr(c - 2) + 8, a3 = f + c * 16, a7 = f + F7O + (c & 1) * 1088 + (c >> 1) * 16;
#pragma unroll 1
  for (int h = 0;; h++) {
    const uint2 p0 = lds64(a2);
    const uint4 p1 = lds128(a1), c0 = lds128(a0);
    const uint32_t raw[9] = {p0.x, p0.y, p1.x, p1.y, p1.z, p1.w, c0.x, c0.y, c0.z};
    uint32_t od[8], G[8], F[4];
#pragma unroll
    for (int j = 0; j < 8; j++) { od[j] = __byte_perm(raw[j], raw[j + 1], 0x5432); G[j] = hadd2(raw[j], od[j]); }
    sts128(a3, hadd2(G[4], od[3]), hadd2(G[5], od[4]), hadd2(G[6], od[5]), hadd2(G[7], od[6]));
#pragma unroll
    for (int j = 0; j < 4; j++) F[j] = hadd2(hadd2(G[j + 1], raw[j + 3]), G[j + 2]);
    sts128(a3 + F5O, F[0], F[1], F[2], F[3]);
    if (h == 2) break;
#pragma unroll
    for (int j = 0; j < 4; j++) F[j] = hadd2(F[j], hadd2(od[j], od[j + 3]));
    sts128(a7, F[0], F[1], F[2], F[3]);
    const int q = (c + 1) & 127;
#pragma unroll
    for (int j = 0; j < 4; j++) F[j] = q ? hadd2(F[j], hadd2(raw[j], raw[j + 4])) : 0;
    sts128(f + F9O + (q & 1) * 1088 + (q >> 6) * 544 + (q & 62) * 8, F[0], F[1], F[2], F[3]);
    a0 += 256; a1 += 256; a2 += 256; a3 += 1024; a7 += 544; c += 64;
  }
}

template <int NS, int D>
__device__ __forceinline__ void toep(uint32_t* v, uint32_t a, uint32_t z) {
  uint32_t e = lds32(a + (uint32_t)(-D * 2));
#pragma unroll
  for (int s = 0; s < NS; s++) {
    v[4 * s] = lds32(a + s * D * 4);
    const uint32_t x = lds32(a + (uint32_t)(s * D * 4 + D * 2));
    v[4 * s + 3] = v[4 * s] ^ z;
    v[4 * s + (D > 0 ? 2 : 1)] = s ? e ^ z : e;
    v[4 * s + (D > 0 ? 1 : 2)] = x;
    e = x;
  }
}
#define V4(v, s) v[4 * (s)], v[4 * (s) + 1], v[4 * (s) + 2], v[4 * (s) + 3]
#define PK2(a, i) pack(a[4 * (i)], a[4 * (i) + 1]), pack(a[4 * (i) + 2], a[4 * (i) + 3])

__device__ __forceinline__ void conv(uint32_t sb, int w, int lane, uint32_t bud, long long tstart) {
  const int g = lane >> 2, t = lane & 3, w2 = w & 1, h = w >> 1;
  uint32_t u = sb + OFF_U, f = sb + OFF_F, kt = sb + OFF_KT;
  const uint32_t z = lds32(kt + 16384);
  const uint32_t on = (16 + 16 * w2 + 288 * h + g - 2 * t) * 4;
  const uint32_t oa = ((lane >> 4) * 2 + ((lane >> 2) & 1)) * 256 + (lane & 8) * 16 + (((lane & 3) * 2 + (w2 ^ ((lane >> 2) & 1))) << 4);
  const uint32_t ob = w2 * 256 + (lane & 1) * 128 + ((((lane & 15) >> 1) ^ w2 ^ ((lane & 1) * 4)) << 4), ts = h ? UPS : 512;
  const uint32_t oc = 7168 + (2 * w + ((lane >> 3) & 1)) * 256 + (lane >> 4) * 128 + (((lane & 7) ^ ((lane >> 3) & 1)) << 4);
  uint64_t dn = mkdesc(u + 128 + 2 * UPS, UPS / 16, 8, 0), d1 = mkdesc(f - 512, 8, 32, 0), d2 = mkdesc(f + F7O, 8, 34, 0);
  MWAIT(sb + OFF_BAR + B_PD);
  uint32_t raw[13];
#pragma unroll
  for (int i = 0; i < 13; i++) raw[i] = lds32(kt + on - 32 + i * 32);
#pragma unroll 1
  for (int c = 0; c < 5; c++) {
    float an[32], a1[24], a2[16];
    uint32_t vn[24], vf[24];
    uint32_t pn = kt + on, p1 = kt + on + (T3O + 80 - 224 * h) * 4, p2 = kt + on + (T7O - 16 - 256 * h) * 4;
    asm volatile("" : "+l"(dn), "+l"(d1), "+l"(d2));
#pragma unroll
    for (int k = 0; k < 3; k++) {
      if (k) toep<6, 16>(vn, pn, z);
      else {
#pragma unroll
        for (int i = 0; i < 6; i++) { vn[4 * i] = raw[2 * i + 1] ^ z; vn[4 * i + 1] = raw[2 * i + 2] ^ z; vn[4 * i + 2] = raw[2 * i] + z; vn[4 * i + 3] = raw[2 * i + 1] + z; }
#pragma unroll
        for (int i = 0; i < 24; i++) asm volatile("" : "+r"(vn[i])::"memory");
      }
      WG_FENCE();
#pragma unroll
      for (int a = 0; a < 6; a++) wg_rs_64(an, V4(vn, a), dadd(dn, -((a & 1) * 2 * (int)(UPS / 16) + (a >> 1))), a ? 1 : k);
      WG_COMMIT();
      WG_WAIT(1);
      if (k == 2) break;
      if (k) { PIN(a1, 4); a1[0] = a1[1] = a1[2] = a1[3] = 0.f; PIN(a1, 4); }
      toep<2, -16>(vf, p1, z); toep<2, -16>(vf + 8, p1 + (T5O - T3O) * 4, z); toep<2, -16>(vf + 16, p2, z);
      WG_FENCE();
#pragma unroll
      for (int a = 0; a < 4; a++) wg_rs_48(a1, V4(vf, a), dadd(d1, 16 * (a & 1) + (a >> 1) * (F5O / 16)), a + k);
      wg_rs_32(a2, V4(vf, 4), d2, k); wg_rs_32(a2, V4(vf, 5), dadd(d2, 16), 1);
      WG_COMMIT();
      WG_WAIT(1);
      pn += 384; p1 -= 128; p2 += (T9O - T7O) * 4;
      dn = dadd(dn, -3); d1 = dadd(d1, 32); d2 = dadd(d2, (F9O - F7O) / 16);
    }
#pragma unroll
    for (int i = 0; i < 13; i++) raw[i] = lds32(kt + on + 4096 - 32 + i * 32);
    sts32(sb + OFF_KV + 4 * c, __byte_perm(lds32(kt + (T5O + 127) * 4), 0, 0x1010));
    PIN(a1, 24); PIN(a2, 16);
    uint32_t q1[12], q2[8];
#pragma unroll
    for (int i = 0; i < 12; i++) { q1[i] = pack(a1[2 * i], a1[2 * i + 1]); asm volatile("" : "+r"(q1[i])::"memory"); }
#pragma unroll
    for (int i = 0; i < 8; i++) { q2[i] = pack(a2[2 * i], a2[2 * i + 1]); asm volatile("" : "+r"(q2[i])::"memory"); }
    dn = dadd(dn, USZ / 16 + 6); d1 = dadd(d1, FSZ / 16 - 64); d2 = dadd(d2, FSZ / 16 - (F9O - F7O) / 8);
    const uint32_t o1 = (h ? f : kt) + oa, o2 = (h ? u + 640 : f + 4096) + ob + (lane >> 4) * ts;
    MWAIT(sb + OFF_BAR + B_PD + 8 * min(c + 1, 4));
    WG_WAIT(0);
    PIN(an, 32);
    BAR_SYNC(3, 128);
    stsm4(o2, q1[0], q1[1], q1[2], q1[3]); stsm4(o2 + 2 * ts, q1[4], q1[5], q1[6], q1[7]);
    stsm4(f + oc, q2[0], q2[1], q2[4], q2[5]);
    if (!h) { stsm4(o2 + 2048, q1[8], q1[9], q1[10], q1[11]); stsm4(f + oc + 2048, q2[2], q2[3], q2[6], q2[7]); }
#pragma unroll
    for (int i = 0; i < 8; i += 2) stsm4t(o1 + i * 512, PK2(an, i), PK2(an, i + 1));
    __syncwarp();
    if (elect()) { mbar_arrive(sb + OFF_BAR + B_MD + 8 * c); if (w == 0) STAMP(17 + c); }
    u += USZ; f += FSZ; kt += 4096;
  }
}

__device__ __forceinline__ void merge(uint32_t sb, int i, uint32_t& bud, uint4* dst, long long tstart) {
  const int c0 = (i & 48) + ((i & 7) ^ ((i >> 4) & 1)) * 2 + ((i >> 3) & 1), cu = c0 + 28;
  const uint32_t o0 = i * 16, o1 = ((cu & 112) + (cu & 1) * 8 + (((cu >> 1) & 7) ^ ((cu >> 4) & 1))) * 16 - 1024, o2 = (i ^ ((i >> 1) & 4)) * 16;
  const uint32_t o3 = 640 - 2 * 2 * UPS + (i >> 5) * UPS + (o2 & 511), o4 = uadr(c0) - 512, o5 = uadr(c0 - 1) - 504;
  uint32_t u = sb + OFF_U, f = sb + OFF_F, kt = sb + OFF_KT + o0;
#pragma unroll 1
  for (int c = 0; c < 5; c++) {
    if (c == 4) BAR_ARRIVE(9, 96);
    MWAIT(sb + OFF_BAR + B_MD + 8 * c);
    const uint32_t kv = lds32(sb + OFF_KV + 4 * c);
#pragma unroll
    for (int it = 0; it < 4; it++) {
      const uint32_t fi = f + it * 1024;
      uint4 s = make_uint4(0, 0, 0, 0);
      if (it) s = lds128(fi + o2 + 3072);
      if (it >= 2) {
        const uint2 p = lds64(u + o5 + it * 256);
        const uint4 q = lds128(u + o4 + it * 256);
        uint4 v = lds128(fi + o0 + 5120);
        if (it == 3) v = add4(v, lds128(f + o0 + 9216));
        v.x = hfma2(kv, hadd2(p.x, __byte_perm(p.x, p.y, 0x5432)), v.x); v.y = hfma2(kv, hadd2(p.y, __byte_perm(p.y, q.x, 0x5432)), v.y);
        v.z = hfma2(kv, hadd2(q.x, __byte_perm(q.x, q.y, 0x5432)), v.z); v.w = hfma2(kv, hadd2(q.y, __byte_perm(q.y, q.z, 0x5432)), v.w);
        s = add4(s, add4(v, lds128(u + o3 + it * 2 * UPS)));
      }
      if (it) s = add4(s, lds128(fi + o1));
      else if (c0 >= 36) s = lds128(fi + o1);
      s = add4(s, lds128(kt + it * 1024));
      asm volatile("st.relaxed.gpu.global.v4.u32 [%0],{%1,%2,%3,%4};" ::"l"(dst + it * 64), "r"(~s.x), "r"(~s.y), "r"(~s.z), "r"(~s.w) : "memory");
    }
    dst += 256; kt += 4096;
    u += USZ; f += FSZ;
  }
}

__device__ __forceinline__ void kwg(const uint32_t* r, const uint32_t* gt, uint32_t sb, int w, int lane, long long tstart) {
  const int tid = w * 32 + lane, g = lane >> 2, t = lane & 3;
  uint32_t pp[10];
  const uint4 g0 = ldg128(gt + tid * 8), g1 = ldg128(gt + tid * 8 + 4);
  const uint32_t ge[7] = {g0.x, g0.y, g0.z, g0.w, g1.x, g1.y, g1.z};
  ST4(tid == 0, 8);
  asm volatile("setmaxnreg.inc.sync.aligned.u32 136;");
  BAR_SYNC(1, 512);
  asm volatile("barrier.cluster.arrive.relaxed.aligned;" ::: "memory");
#pragma unroll
  for (int i = 0; i < 10; i++) pp[i] = r[2 * i] | r[2 * i + 1] << 16;
  const uint32_t dd = r[20] | __shfl_sync(0xffffffffu, r[20], lane + 14) << 16;
  ST4(tid == 0 && pp[0] != 0x12345, 10);
  uint32_t sa = sb + OFF_KA0, sw = sb + OFF_KB0;
  const uint32_t ko = w * 4096 + t * 128 + ((g ^ (t * 8)) << 2);
  const uint32_t ao = (tid >> 6) * 8192 + (tid & 63) * 16, wo = (tid >> 6) * 6144 + (tid & 63) * 16;
  float acc[24];
  uint32_t bud = 16;
  KG k;
#pragma unroll 1
  for (int lc = -1;; lc++) {
    float kv[14];
    const uint32_t dn = __shfl_sync(0xffffffffu, dd, lc + 1);
    if (lc >= 2) {
#pragma unroll
      for (int e = 0; e < 7; e++) { const uint32_t ix = sa + (ge[e] & 0xffff); kv[e] = ldsf(ix); kv[e + 7] = ldsf(ix + 8192); }
    }
    if ((unsigned)lc < 5u) kgen_w(k, sw + wo);
    if (lc >= 2) {
#pragma unroll
      for (int e = 0; e < 7; e++) kv[e] += kv[e + 7];
      PIN(kv, 7);
      __syncwarp();
      if (elect()) mbar_arrive(sb + OFF_BAR + B_KG - 16 + 8 * min(lc, 5));
#pragma unroll
      for (int e = 0; e < 7; e++) { const uint32_t dst = sb + OFF_KT - 8192 + lc * 4096 + (ge[e] >> 16), hb = pack(kv[e], 0.f); sts16(dst, hb); sts16(dst + 6, hb); }
      if (tid == 0) STAMP(25 + lc);
      if (lc == 6) break;
    }
    if ((unsigned)lc < 5u) {
      if (lc >= 2) MWAIT(sb + OFF_BAR + B_KG - 16 + 8 * lc);
      kgen_e(k, sa + ao);
      ST4(tid == 0, 12 + lc);
    }
    if (lc < 4) {
      kgen_p(k, pp[0], pp[1], dn);
#pragma unroll
      for (int i = 0; i < 8; i++) pp[i] = pp[i + 2];
      if (lc < 0) continue;
    }
    FENCE_ASYNC_SH();
    const uint64_t da = mkdesc(sa, 64, 128, 0), db = mkdesc(sw, 64, 128, 0);
    sa ^= (sb + OFF_KA0) ^ (sb + OFF_KA1); sw ^= (sb + OFF_KB0) ^ (sb + OFF_KB1);
    WG_WAIT(0);
    PIN(acc, 24);
    if (lc) {
      if (tid == 0) acc[0] += bhi(dn);
#pragma unroll
      for (int i = 0; i < 3; i++) {
        stsf(sa + ko + i * 512, (w >> 1) ? acc[12 + 4 * i] : acc[4 * i]);
        stsf(sa + (ko ^ 80) + i * 512, (w >> 1) ? acc[13 + 4 * i] : acc[4 * i + 1]);
        stsf(sa + (ko ^ 32) + i * 512, (w >> 1) ? acc[14 + 4 * i] : acc[4 * i + 2]);
        stsf(sa + (ko ^ 112) + i * 512, (w >> 1) ? acc[15 + 4 * i] : acc[4 * i + 3]);
      }
    }
    BAR_SYNC(3, 128);
    ST4(tid == 0, 17 + lc);
    if (lc < 5) {
      WG_FENCE();
#pragma unroll
      for (int s = 0; s < 8; s++) wg_ss_48(acc, dadd(da, s * 8), dadd(db, s * 8), s);
      WG_COMMIT();
    }
  }
  WG_WAIT(0);
  FENCE_ASYNC_SH();
  BAR_SYNC(3, 128);
  asm volatile("barrier.cluster.wait.aligned;" ::: "memory");
  if (elect()) mbar_arrive(sb + OFF_BAR + B_KD);
  asm volatile("setmaxnreg.inc.sync.aligned.u32 152;");
  conv(sb, w, lane, bud, tstart);
}

__device__ __forceinline__ void aux(const Ptrs& Q, const Params& P, uint32_t sb, int m, int nt, int kh, int w, int lane, long long tstart) {
  const uint32_t bb = sb + OFF_BAR;
  const int n = kh * 4 + nt, tid = w * 32 + lane;
  const int ch0 = blockIdx.x * 5, ta = tA(n), th = tH(n), w2 = w & 1;
  uint32_t bud = 16;
  unsigned ep;
  uint4 tb;
  const int col = 8 * lane + (lane < 24 ? ta : th - 192);
  asm volatile("setmaxnreg.dec.sync.aligned.u32 72;");
  ST4(tid == 0, 5);
  if (w == 0) {
    if (lane < 13) mbar_init(bb + (lane < 8 ? lane * 8 : lane < 12 ? B_E1 - 64 + lane * 8 : B_CS), lane >> 2 == 2 ? 8 : 0, lane < 8 ? lane & 1 ? 14336 : 30720 : lane < 12 ? 0 : 17280);
    FENCE_ASYNC_SH();
    BAR_ARRIVE(0, 288);
    BAR_ARRIVE(1, 512);
    asm volatile("barrier.cluster.arrive.relaxed.aligned;" ::: "memory");
    if (elect()) {
      const int skip = skipq(nt, kh);
      tma2d(sb + OFF_A, &P.mx, bb + B_F1, 0, m * 128);
      uint32_t xs = 16384;
#pragma unroll 1
      for (int q = 0; q < 20; q++) {
        const uint32_t d = sb + OFF_B0 + (q & 3) * 16384, fb = bb + B_F1 + 8 * q;
        wait_tma<1>(bud, q >= 4 ? fb + (B_E1 - B_F1 - 32) : 0, d, &P.mw1a, fb, ta, q * 32, d + 12288, &P.mw1b, th);
        if ((q & 1) && q < 19) { tma2d(sb + OFF_A + xs, &P.mx, fb + 8, q * 32 + 32, m * 128); xs = xs == 32768 ? 0 : xs + 16384; }
        if (q == 1) tma2d(sb + OFF_CS, &P.mcs, bb + B_CS, n * 216, m * 40);
        if (q == 5) FENCE_ASYNC_SH();
      }
      uint32_t d = sb + OFF_W, fb = bb + B_F2;
      const uint32_t fs = fb + 8 * skip;
      const int ca = nt * 160 + (nt & 1) * 32, cb = nt * 160 + (~nt & 1) * 128;
#define W2NEXT() fb += 8; d = d == sb + OFF_W + 5 * 12288 ? sb + OFF_W : d + 12288
#pragma unroll 1
      for (int c = 0; c < 6; c++) {
        wait_tma<0>(bud, c < 4 ? bb + B_E1 + 8 * 19 : bb + B_KD, d + c * 12288, &P.mw2a, fb + c * 8, ca, ta + c * 32, d + c * 12288 + 8192, &P.mw2b, cb);
        ST4(c == 0, 1); ST4(c == 3, 2); ST4(c == 5, 4);
      }
      fb += 48;
      int kh2 = th;
#pragma unroll 1
      for (int tq = 1;; tq++) {
        if (fb != fs) wait_tma<0>(bud, fb + (B_E2 - B_F2 - 48), d, &P.mw2a, fb, ca, kh2, d + 8192, &P.mw2b, cb);
        if (tq == 4) break;
        W2NEXT();
        const int tn = tord(n, tq), k0 = tA(tn);
        kh2 = tH(tn);
#pragma unroll 1
        for (int k = k0; k < k0 + 192; k += 32) {
          wait_tma<0>(bud, fb + (fb == fs + 48 ? B_E2 - B_F2 - 56 : B_E2 - B_F2 - 48), d, &P.mw2a, fb, ca, k, d + 8192, &P.mw2b, cb);
          W2NEXT();
        }
      }
    }
    __syncwarp();
    asm volatile("barrier.cluster.wait.aligned;" ::: "memory");
    return;
  } else {
    if (w < 3 && lane < 36 - 8 * w) tb = ldg128(w == 1 ? Q.arr[6] + col : Q.arr[7] + nt * 160 + 8 * lane);
    asm volatile("ld.global.cg.u32 %0,[%1];" : "=r"(ep) : "l"(Q.S->ep + blockIdx.x * 32 + lane) : "memory");
  }
  BAR_SYNC(1, 512);
  asm volatile("barrier.cluster.arrive.relaxed.aligned;" ::: "memory");
  const int skip = skipq(nt, kh);
  ep++;
  {
    float cs[8] = {0.f, 0.f, 0.f, 0.f, 0.f, 0.f, 0.f, 0.f};
    MWAIT(bb + B_CS);
    ST4(tid == 32, 9);
    uint32_t a = sb + OFF_CS + w * 432 + lane * 16;
    if (w == 1) add8(cs, lds128(a - 432));
    uint4 cv[7];
#pragma unroll
    for (int i = 0; i < 7; i++) cv[i] = lds128(a + i * 1296);
#pragma unroll
    for (int i = 0; i < 7; i++) { add8(cs, cv[i]); if (i < 6) cv[i] = lds128(a + (i + 7) * 1296); }
#pragma unroll
    for (int i = 0; i < 6; i++) add8(cs, cv[i]);
    const uint32_t ca = sb + OFF_CB + lane * 16;
    if (w > 1 && lane < 28) { sts128f(ca + w2 * 896, cs[0], cs[1], cs[2], cs[3]); sts128f(ca + w2 * 896 + 448, cs[4], cs[5], cs[6], cs[7]); }
    BAR_SYNC(6, 96);
    ST4(tid == 32, 11);
    asm volatile("barrier.cluster.wait.aligned;" ::: "memory");
    const uint32_t pp[4] = {tb.x, tb.y, tb.z, tb.w};
    if (w == 1) {
      if (lane < 27) {
        const float4 v0 = lds128f(ca), v1 = lds128f(ca + 448), v2 = lds128f(ca + 896), v3 = lds128f(ca + 1344);
        float* d = Q.S->cs + n * 216 + 8 * lane;
        asm volatile("red.relaxed.gpu.global.add.v4.f32 [%0],{%1,%2,%3,%4};" ::"l"(d + (ep & 1) * 1728), "f"(cs[0] + v0.x + v2.x), "f"(cs[1] + v0.y + v2.y), "f"(cs[2] + v0.z + v2.z), "f"(cs[3] + v0.w + v2.w) : "memory");
        asm volatile("red.relaxed.gpu.global.add.v4.f32 [%0],{%1,%2,%3,%4};" ::"l"(d + (ep & 1) * 1728 + 4), "f"(cs[4] + v1.x + v3.x), "f"(cs[5] + v1.y + v3.y), "f"(cs[6] + v1.z + v3.z), "f"(cs[7] + v1.w + v3.w) : "memory");
        if (m == 0) { float4* z = (float4*)(d + (~ep & 1) * 1728); z[0] = z[1] = make_float4(0.f, 0.f, 0.f, 0.f); }
      }
      BAR_ARRIVE(2, 320);
      if (elect()) {
        __threadfence();
        asm volatile("red.relaxed.gpu.global.add.u32 [%0],1;" ::"l"(Q.S->cnt + 160) : "memory");
        POLL(Q.S->cnt + 160, ep * 128);
        STAMP(12);
      }
      __syncwarp();
      if (lane < 28) {
        const float4* s = (const float4*)(Q.S->cs + (ep & 1) * 1728 + col);
        const float4 s0 = __ldcg(s), s1 = __ldcg(s + 1);
        const uint32_t h0 = pack(s0.x, s0.y), h1 = pack(s0.z, s0.w), h2 = pack(s1.x, s1.y), h3 = pack(s1.z, s1.w), d = sb + OFF_RK + lane * 144;
        MWAIT(bb + B_E1 + 8 * 15);
        sts32(sb + OFF_ST + 512, (ep & 1) * 640);
        sts128(d, h0, h1, h2, h3); sts128(d + 32, h0, h1, h2, h3);
        sts128(d + 16, pack(s0.x - blo(h0), s0.y - bhi(h0)), pack(s0.z - blo(h1), s0.w - bhi(h1)), pack(s1.x - blo(h2), s1.y - bhi(h2)), pack(s1.z - blo(h3), s1.w - bhi(h3)));
        sts128(d + 48, tb.x, tb.y, tb.z, tb.w); sts128(d + 64, tb.x, tb.y, tb.z, tb.w);
        sts128(d + 80, 0, 0, 0, 0); sts128(d + 96, 0, 0, 0, 0); sts128(d + 112, 0, 0, 0, 0); sts128(d + 128, 0, 0, 0, 0);
        FENCE_ASYNC_SH();
      }
      MWAIT(bb + B_UB);
      BAR_ARRIVE(7, 288);
      if (lane == 0) STAMP(14);
    } else {
      if (w == 2) {
        if (lane < 20) {
          sts128f(sb + OFF_B2 + lane * 32, 0.5f * blo(pp[0]), 0.5f * bhi(pp[0]), 0.5f * blo(pp[1]), 0.5f * bhi(pp[1]));
          sts128f(sb + OFF_B2 + lane * 32 + 16, 0.5f * blo(pp[2]), 0.5f * bhi(pp[2]), 0.5f * blo(pp[3]), 0.5f * bhi(pp[3]));
        }
        if (elect()) asm volatile("cp.async.bulk.prefetch.L2.global [%0],17280;" ::"l"(Q.w2 + blockIdx.x * 17280) : "memory");
      } else {
        BAR_SYNC(2, 320);
      }
      if (w == 3 && elect()) {
        __threadfence();
        asm volatile("red.relaxed.gpu.global.add.u32 [%0],1;" ::"l"(Q.S->cnt) : "memory");
        STAMP(8);
        POLL(Q.S->cnt, ep * 128);
        STAMP(11);
        FENCE_ASYNC_G(); FENCE_ASYNC_SH();
#pragma unroll 1
        for (int c = 0; c < 5; c++) bulk_ld(sb + OFF_U + c * USZ, Q.S->u + (ch0 + c) * 592, USZ, bb + B_UB + 8 * c);
        bulk_ld(sb + OFF_CB, Q.S->stats + m * 128, 2048, bb + B_UB);
      }
      __syncwarp();
#pragma unroll 1
      for (int c = 0; c < 5; c++) {
        MWAIT(bb + B_UB + 8 * c);
        if (c == 1) {
          uint4* z = Q.S->sT + (~ep & 1) * 163840 + blockIdx.x * 1280 + tid - 64;
#pragma unroll 4
          for (int k = 0; k < 20; k++) z[k * 64] = make_uint4(0, 0, 0, 0);
          MWAIT(bb + B_KD);
        }
        prep(sb + OFF_U + c * USZ, sb + OFF_F + c * FSZ, w2 * 32 + lane);
        FENCE_ASYNC_SH();
        __syncwarp();
        if (elect()) mbar_arrive(bb + B_PD + 8 * c);
      }
      if (tid == 64) STAMP(13);
    }
  }
  if (w == 1) {
    unsigned* fp = Q.S->flagH + (m * 2 + kh) * 8;
#define HFLAG(v) asm volatile("cp.async.bulk.wait_group 0;" ::: "memory"); FENCE_ASYNC_G(); asm volatile("st.relaxed.gpu.global.u32 [%0],%1;" ::"l"(fp + nt), "r"(v) : "memory")
    uint4* own = Q.S->H + (size_t)(m * 8 + n) * 3584;
    BAR_SYNC(4, 288);
    if (elect()) { bulk_st(own, sb + OFF_HST, 28672); HFLAG(2 * ep - 1); }
    __syncwarp();
    BAR_SYNC(5, 288);
    if (elect()) {
      bulk_st(own + 1792, sb + OFF_HST + 28672, 28672);
      STAMP(3);
      int f0 = 2 * ep - 2, f1 = f0, f2 = f0, f3 = f0;
      uint32_t fb = bb + B_F2 + 56;
      const uint32_t fs = bb + B_F2 + 8 * skip;
#pragma unroll 1
      for (int hq = 2; hq < 8; hq++) {
        const int tn = tord(n, hq >> 1);
        const uint4* src = Q.S->H + (size_t)(m * 8 + tn) * 3584 + (hq & 1) * 1536;
        uint32_t d = sb + OFF_HST + (hq & 1) * 24576;
        if (hq == 3) { HFLAG(2 * ep); STAMP(5); }
        while ((tn & 2 ? (tn & 1 ? f3 : f2) : (tn & 1 ? f1 : f0)) - (int)(2 * ep) + (~hq & 1) < 0 && ++bud < 2000000)
          asm volatile("ld.relaxed.gpu.global.v4.u32 {%0,%1,%2,%3},[%4];" : "=r"(f0), "=r"(f1), "=r"(f2), "=r"(f3) : "l"(fp) : "memory");
        FENCE_ASYNC_G();
#pragma unroll
        for (int c = 0; c < 3; c++) wait_ld(bud, fb + (B_E2 - B_F2 - 56) + 8 * c, d + c * 8192, src + c * 512, fb + 8 * c);
        if ((hq & 1) && fb + 24 != fs) wait_ld(bud, fb + (fb == fs + 32 ? B_E2 - B_F2 - 40 : B_E2 - B_F2 - 32), d + 24576, src + 1536, fb + 24);
        fb += 24 + (hq & 1) * 8;
      }
    }
    __syncwarp();
    BAR_SYNC(9, 96);
    if (elect()) {
      FENCE_ASYNC_SH();
      mbar_arrive_cl(mapa(bb + B_XR, kh ^ 1));
      tma3d(sb + OFF_XO, &P.mxo, bb + B_SF, nt * 160, kh * 8, m * 8);
    }
    return;
  }
  if (w == 2) Q.S->ep[blockIdx.x * 32 + lane] = ep;
  merge(sb, tid - 64, bud, Q.S->sT + (ep & 1) * 163840 + blockIdx.x * 1280 + tid - 64, tstart);
  if (tid == 64) STAMP(22);
}

__global__ void __cluster_dims__(2, 1, 1) __launch_bounds__(512, 1) fused_kernel(const __grid_constant__ Ptrs Q, const __grid_constant__ Params P) {
  extern __shared__ __align__(1024) unsigned char smem[];
  long long tstart = 0;
  uint32_t sb = (uint32_t)__cvta_generic_to_shared(smem);
  int wid = __shfl_sync(0xffffffffu, threadIdx.x >> 5, 0);
  const int lane = threadIdx.x & 31;
  uint32_t pre[21];
  if (wid < 8) {
    pre[20] = lntok(blockIdx.x, lane >> 2);
    const char* xp = Q.x + pre[20] * 1280 + wid * 160 + (lane & 3) * 8;
    const char* xq = xp + (lane & 3) * 8;
    const uint4 a0 = ldg128(xq), b0 = ldg128(xq + 2560), a1 = ldg128(xq + 64), b1 = ldg128(xq + 2624);
    const uint2 a2 = ldg64(xp + 128), b2 = ldg64(xp + 2688);
    pre[0] = a0.x; pre[1] = a0.y; pre[2] = a0.z; pre[3] = a0.w; pre[4] = a1.x; pre[5] = a1.y; pre[6] = a1.z; pre[7] = a1.w; pre[8] = a2.x; pre[9] = a2.y;
    pre[10] = b0.x; pre[11] = b0.y; pre[12] = b0.z; pre[13] = b0.w; pre[14] = b1.x; pre[15] = b1.y; pre[16] = b1.z; pre[17] = b1.w; pre[18] = b2.x; pre[19] = b2.y;
  } else if (wid < 12) {
    const int tid = threadIdx.x - 256;
    pre[20] = ldg16(Q.arr[4 + (lane >> 4)] + blockIdx.x * 5 + min(lane & 15, 4));
#pragma unroll
    for (int i = 0; i < 20; i++) pre[i] = ldg16(Q.arr[i & 3] + blockIdx.x * 640 + tid + (i >> 2) * 128);
  }
  asm volatile("mov.u32 %0,%0;" : "+r"(wid));
  const int kh = blockIdx.x & 1, p = blockIdx.x >> 1;
  const int q7 = ((p - 36) * 37) >> 8;
  const int gp = p < 4 ? 15 : p < 36 ? (p - 4) & 7 : p - 28 - 7 * q7, gi = p < 4 ? p : p < 36 ? (p - 4) >> 3 : q7;
  const int nt = (gp & 1) * 2 + (gi >> 1), m = (gp & 14) + (gi & 1);
  if (wid < 8) {
    consumer(Q, pre, sb, m, nt, kh, wid, lane, tstart);
  } else if (wid < 12) {
    kwg(pre, Q.gt, sb, wid - 8, lane, tstart);
  } else {
    aux(Q, P, sb, m, nt, kh, wid - 12, lane, tstart);
  }
}

typedef CUresult (*EncFn)(CUtensorMap*, CUtensorMapDataType, cuuint32_t, void*, const cuuint64_t*, const cuuint64_t*, const cuuint32_t*, const cuuint32_t*, CUtensorMapInterleave, CUtensorMapSwizzle, CUtensorMapL2promotion, CUtensorMapFloatOOBfill);
static void mk(EncFn enc, CUtensorMap* tm, const void* p, int rank, cuuint64_t d0, cuuint64_t d1, cuuint64_t d2, cuuint64_t s1, cuuint64_t s2, cuuint32_t b0, cuuint32_t b1, cuuint32_t b2, CUtensorMapSwizzle sw = CU_TENSOR_MAP_SWIZZLE_128B) {
  cuuint64_t gd[3] = {d0, d1, d2}, gs[2] = {s1, s2};
  cuuint32_t bd[3] = {b0, b1, b2}, es[3] = {1, 1, 1};
  enc(tm, CU_TENSOR_MAP_DATA_TYPE_BFLOAT16, rank, (void*)p, gd, gs, bd, es, CU_TENSOR_MAP_INTERLEAVE_NONE, sw, CU_TENSOR_MAP_L2_PROMOTION_L2_128B, CU_TENSOR_MAP_FLOAT_OOB_FILL_NONE);
}

extern "C" void kernel_launch(void* const* d_in, const int* in_sizes, int n_in, void* d_out, int out_size) {
  Params P;
  Ptrs Q;
  for (int i = 0; i < 6; i++) Q.arr[i] = (const unsigned short*)d_in[1 + i];
  Q.arr[6] = (const unsigned short*)d_in[9]; Q.arr[7] = (const unsigned short*)d_in[11];
  Q.x = (const char*)d_in[0]; Q.w2 = (const char*)d_in[10]; Q.out = (char*)d_out;
  void* fn = nullptr; cudaDriverEntryPointQueryResult qr;
  cudaGetDriverEntryPoint("cuTensorMapEncodeTiled", &fn, cudaEnableDefault, &qr);
  EncFn enc = (EncFn)fn;
  cudaGetSymbolAddress((void**)&Q.S, g_scr);
  cudaGetSymbolAddress((void**)&Q.gt, g_gt);
  mk(enc, &P.mx, Q.x, 2, 640, 2048, 1, 1280, 0, 64, 128, 1);
  mk(enc, &P.mw1a, d_in[8], 3, 1728 - 128, 640, 3, 3456, 128, 64, 32, 3);
  mk(enc, &P.mw1b, d_in[8], 2, 1728, 640, 1, 3456, 0, 32, 32, 1);
  mk(enc, &P.mcs, d_in[8], 2, 1728, 640, 1, 3456, 0, 216, 40, 1, CU_TENSOR_MAP_SWIZZLE_NONE);
  mk(enc, &P.mw2a, Q.w2, 3, 640 - 64, 1728, 2, 1280, 128, 64, 32, 2);
  mk(enc, &P.mw2b, Q.w2, 2, 640, 1728, 1, 1280, 0, 32, 32, 1);
  mk(enc, &P.mxo, Q.x, 3, 640, 16, 128, 1280, 20480, 168, 8, 8, CU_TENSOR_MAP_SWIZZLE_NONE);
  cudaFuncSetAttribute(fused_kernel, cudaFuncAttributeMaxDynamicSharedMemorySize, SMEM_BYTES);
  fused_kernel<<<128, 512, SMEM_BYTES, cudaStreamPerThread>>>(Q, P);
}
```
